```python
import torch

def _softmax(x, axis=-1):
    return torch.softmax(x, dim=axis)
def _gelu(x):
    return torch.nn.functional.gelu(x, approximate="tanh")
def _silu(x):
    return torch.nn.functional.silu(x)
def _sigmoid(x):
    return torch.sigmoid(x)
def _layernorm(x, axis=-1, eps=1e-5):
    m = x.mean(dim=axis, keepdim=True)
    v = x.var(dim=axis, keepdim=True, unbiased=False)
    return (x - m) / torch.sqrt(v + eps)
def _scatter_add(tgt, idx, src, axis=0):
    return tgt.clone().index_add_(axis, idx, src)
def _segment_sum(src, seg, n):
    out = torch.zeros((n,) + src.shape[1:], dtype=src.dtype)
    return out.index_add_(0, seg, src)
def _pad(x, pw):
    flat = tuple(v for pair in reversed(pw) for v in pair)
    return torch.nn.functional.pad(x, flat)

kernel_name = 'sequential_preLN__compressed_kv_cla__glu_gated_glu__decode'

def setup_inputs():

    _w = (lambda a: (lambda t: t.to(torch.bfloat16) if t.is_floating_point() else t)(torch.as_tensor(a)))
    def _A_setup():
        B, H, Sq, Sk, D, M = 1, 16, 1, 8192, 256, 448
        Dc = 4 * D
        return {
            "x": _w((lambda *s: torch.randn(*s, dtype=torch.bfloat16) * 0.05)(B, Sq, M)),
            "c_kv": _w((lambda *s: torch.randn(*s, dtype=torch.bfloat16) * 0.4)(B, Sk, Dc)),
            "w_q": _w((lambda *s: torch.randn(*s, dtype=torch.bfloat16) * 3.2)(M, H, D) * (M ** -0.5)),
            "w_uk": _w((lambda *s: torch.randn(*s, dtype=torch.bfloat16) * 3.2)(Dc, H, D) * (Dc ** -0.5)),
            "w_uv": _w((lambda *s: torch.randn(*s, dtype=torch.bfloat16) * 0.4)(Dc, H, D) * (Dc ** -0.5)),
            "w_o": _w((lambda *s: torch.randn(*s, dtype=torch.bfloat16) * 0.4)(H, D, M) * ((H * D) ** -0.5)),
        }
    _A_in = _A_setup()

    def _B_setup():
        B, S, D, F = 1, 1, 448, 1792
        return {
            "x": _w((lambda *s: torch.randn(*s, dtype=torch.bfloat16) * 0.05)(B, S, D)),
            "w_gate": _w((lambda *s: torch.randn(*s, dtype=torch.bfloat16) * 0.05)(D, F)),
            "w_up": _w((lambda *s: torch.randn(*s, dtype=torch.bfloat16) * 0.05)(D, F)),
            "w_down": _w((lambda *s: torch.randn(*s, dtype=torch.bfloat16) * 0.05)(F, D)),
        }
    _B_in = _B_setup()

    return {
        "A_x": _A_in["x"],
        "A_c_kv": _A_in["c_kv"],
        "A_w_q": _A_in["w_q"],
        "A_w_uk": _A_in["w_uk"],
        "A_w_uv": _A_in["w_uv"],
        "A_w_o": _A_in["w_o"],
        "B_x": _B_in["x"],
        "B_w_gate": _B_in["w_gate"],
        "B_w_up": _B_in["w_up"],
        "B_w_down": _B_in["w_down"],
    }

def reference(A_x, A_c_kv, A_w_q, A_w_uk, A_w_uv, A_w_o, B_x, B_w_gate, B_w_up, B_w_down):
    def _A_ref(x, c_kv, w_q, w_uk, w_uv, w_o):
        B, Sq, M = x.shape[0], x.shape[1], x.shape[2]
        Sk = c_kv.shape[1]
        H, D = w_q.shape[1], w_q.shape[2]
        q = torch.einsum("bqm,mhd->bhqd", x, w_q)
        k = torch.einsum("bkc,chd->bhkd", c_kv, w_uk)
        v = torch.einsum("bkc,chd->bhkd", c_kv, w_uv)
        scores = torch.einsum("bhqd,bhkd->bhqk", q, k) * (D ** -0.5)
        off = Sk - Sq
        qi = torch.arange(Sq)[:, None]
        kj = torch.arange(Sk)[None, :]
        cmask = kj <= (qi + off)
        scores = torch.where(cmask[None, None], scores, -1e9)
        p = _softmax(scores, axis=-1)
        ctx = torch.einsum("bhqk,bhkd->bhqd", p, v)
        return torch.einsum("bhqd,hdm->bqm", ctx, w_o)

    def _B_ref(x, w_gate, w_up, w_down):
        g = torch.einsum("bsd,df->bsf", x, w_gate)
        u = torch.einsum("bsd,df->bsf", x, w_up)
        h = _sigmoid(g) * u
        return torch.einsum("bsf,fd->bsd", h, w_down)

    x = A_x
    h = x + _A_ref(_layernorm(x, axis=-1), A_c_kv, A_w_q, A_w_uk, A_w_uv, A_w_o)
    h2 = h + _B_ref(_layernorm(h, axis=-1), B_w_gate, B_w_up, B_w_down)
    return h2
```

```cpp
#include <cuda_runtime.h>
#include <cuda_bf16.h>
#include <cuda.h>
#include <stdint.h>

namespace {

constexpr int H_ = 16, SK_ = 8192, D_ = 256, M_ = 448, DC_ = 1024, F_ = 1792;
constexpr int NWARPS = 12;
constexpr int NTHREADS = NWARPS * 32;
constexpr int NFCTA = 112;
constexpr int MAXNC = 32;
constexpr int MAXG = 128;
constexpr int MAXCH = 5;
constexpr int MAXUB = 10;
constexpr int MAXSLOT = 10;
constexpr int NSLOT = 20;
constexpr int MAXGR = 56;
#define MLA_SEGMASK 127
#define MLA_WIN 5
#define MLA_WINC 6
constexpr int WIN = MLA_WIN;
#define MLA_WINB 3
constexpr int WINB = MLA_WINB;
#define MLA_WIND 3
constexpr int WIND = MLA_WIND;
constexpr int WINC = MLA_WINC;
#define MLA_DPOLL 9
#define MLA_NINIT 4
constexpr int NINIT = MLA_NINIT;
constexpr float REF_SLACK = 20.f;
constexpr int SPIN_LIMIT = 1 << 15;

typedef unsigned long long u64;

constexpr int O_Q = 0;
constexpr int O_QA = O_Q + 2 * H_ * D_;
constexpr int O_ML = O_QA + H_ * DC_ / 2;
constexpr int O_CTX = O_ML + MAXNC * 8 * H_ * 2;
constexpr int O_X1 = O_CTX + MAXSLOT * H_ * D_;
constexpr int O_X2 = O_X1 + 16 * 8 * 16 * 64;
constexpr int O_ACC = O_X2 + 8 * 16 * 64;
constexpr int O_PART = O_ACC + 8 * 64;
constexpr int O_EPOCH = O_PART + MAXNC * H_ * DC_ / 2;
__device__ __align__(128) u64 g_s[O_EPOCH + 16];

struct Params {
    const __nv_bfloat16* x;
    __nv_bfloat16* out;
    int G, NC;
    int qB, rB, lB;
    int qE, rE, lE;
    int qK, rK;
    unsigned char firstB[H_];
    unsigned char nslot[H_];
};

struct Maps { CUtensorMap m[8]; };

__device__ __forceinline__ uint32_t smem_u32(const void* p) { return (uint32_t)__cvta_generic_to_shared(p); }
__device__ __forceinline__ void mbar_init(uint32_t bar, int cnt) { asm volatile("mbarrier.init.shared::cta.b64 [%0], %1;" ::"r"(bar), "r"(cnt) : "memory"); }
__device__ __forceinline__ void mbar_expect_tx(uint32_t bar, uint32_t bytes) { asm volatile("mbarrier.arrive.expect_tx.shared::cta.b64 _, [%0], %1;" ::"r"(bar), "r"(bytes) : "memory"); }
__device__ __forceinline__ void mbar_arrive(uint32_t bar) { asm volatile("mbarrier.arrive.shared::cta.b64 _, [%0];" ::"r"(bar) : "memory"); }
__device__ __forceinline__ bool mbar_try(uint32_t bar, uint32_t parity) {
    uint32_t ok;
    asm volatile("{\n.reg .pred p;\nmbarrier.try_wait.parity.shared::cta.b64 p, [%1], %2;\nselp.b32 %0, 1, 0, p;\n}\n" : "=r"(ok) : "r"(bar), "r"(parity) : "memory");
    return ok != 0;
}
__device__ __forceinline__ bool mbar_test(uint32_t bar) {
    uint32_t ok;
    asm volatile("{\n.reg .pred p;\nmbarrier.test_wait.parity.shared::cta.b64 p, [%1], 0;\nselp.b32 %0, 1, 0, p;\n}\n" : "=r"(ok) : "r"(bar) : "memory");
    return ok != 0;
}
__device__ __forceinline__ void mbar_wait1(uint32_t bar, uint32_t parity = 0) {
    int lim = 0;
    while (!mbar_try(bar, parity) && ++lim < SPIN_LIMIT) {}
}
__device__ __forceinline__ void mbar_wait(uint32_t bar, uint32_t parity = 0) {
    if (__all_sync(0xffffffffu, mbar_try(bar, parity))) return;
    int lim = 0;
    while (!__all_sync(0xffffffffu, mbar_try(bar, parity)) && ++lim < SPIN_LIMIT) {}
}
__device__ __forceinline__ float ex2(float x) { float y; asm("ex2.approx.ftz.f32 %0, %1;" : "=f"(y) : "f"(x)); return y; }
__device__ __forceinline__ uint32_t mapa(uint32_t addr, uint32_t rank) {
    uint32_t r;
    asm volatile("mapa.shared::cluster.u32 %0, %1, %2;" : "=r"(r) : "r"(addr), "r"(rank));
    return r;
}
__device__ __forceinline__ void st_async_v4(uint32_t addr, uint32_t a, uint32_t b, uint32_t c, uint32_t d, uint32_t bar) {
    asm volatile("st.async.weak.shared::cluster.mbarrier::complete_tx::bytes.v4.b32 [%0], {%1,%2,%3,%4}, [%5];" ::"r"(addr), "r"(a), "r"(b), "r"(c), "r"(d), "r"(bar) : "memory");
}
__device__ __forceinline__ void st_async_v2(uint32_t addr, uint32_t a, uint32_t b, uint32_t bar) {
    asm volatile("st.async.weak.shared::cluster.mbarrier::complete_tx::bytes.v2.b32 [%0], {%1,%2}, [%3];" ::"r"(addr), "r"(a), "r"(b), "r"(bar) : "memory");
}
__device__ __forceinline__ void tma4d(uint32_t dst, const CUtensorMap* tm, int c0, int c1, int c2, int c3, uint32_t bar) {
    asm volatile("cp.async.bulk.tensor.4d.shared::cluster.global.mbarrier::complete_tx::bytes [%0], [%1, {%3, %4, %5, %6}], [%2];" ::"r"(dst), "l"(tm), "r"(bar), "r"(c0), "r"(c1), "r"(c2), "r"(c3) : "memory");
}
__device__ __forceinline__ void prefetch_tm(const CUtensorMap* tm) { asm volatile("prefetch.tensormap [%0];" ::"l"(tm) : "memory"); }
__device__ __forceinline__ void ldsm4(uint32_t (&r)[4], uint32_t addr) {
    asm volatile("ldmatrix.sync.aligned.m8n8.x4.shared.b16 {%0,%1,%2,%3}, [%4];" : "=r"(r[0]), "=r"(r[1]), "=r"(r[2]), "=r"(r[3]) : "r"(addr) : "memory");
}
__device__ __forceinline__ void ldsm4t(uint32_t (&r)[4], uint32_t addr) {
    asm volatile("ldmatrix.sync.aligned.m8n8.x4.trans.shared.b16 {%0,%1,%2,%3}, [%4];" : "=r"(r[0]), "=r"(r[1]), "=r"(r[2]), "=r"(r[3]) : "r"(addr) : "memory");
}
__device__ __forceinline__ void mma16816(float (&c)[4], const uint32_t (&a)[4], uint32_t b0, uint32_t b1) {
    asm volatile("mma.sync.aligned.m16n8k16.row.col.f32.bf16.bf16.f32 {%0,%1,%2,%3}, {%4,%5,%6,%7}, {%8,%9}, {%0,%1,%2,%3};"
                 : "+f"(c[0]), "+f"(c[1]), "+f"(c[2]), "+f"(c[3])
                 : "r"(a[0]), "r"(a[1]), "r"(a[2]), "r"(a[3]), "r"(b0), "r"(b1));
}
__device__ __forceinline__ uint32_t lds32(uint32_t addr) { uint32_t v; asm volatile("ld.shared.b32 %0, [%1];" : "=r"(v) : "r"(addr) : "memory"); return v; }
__device__ __forceinline__ uint4 lds128(uint32_t addr) { uint4 v; asm volatile("ld.shared.v4.b32 {%0,%1,%2,%3}, [%4];" : "=r"(v.x), "=r"(v.y), "=r"(v.z), "=r"(v.w) : "r"(addr) : "memory"); return v; }
__device__ __forceinline__ void bar_compute() { asm volatile("bar.sync 1, 256;" ::: "memory"); }
__device__ __forceinline__ void cluster_wait() { asm volatile("barrier.cluster.wait.acquire.aligned;" ::: "memory"); }

#define GS(off) (g_s + (uint32_t)(off))
__device__ __forceinline__ u64 mk(uint32_t payload, uint32_t tag) { return ((u64)tag << 32) | payload; }
__device__ __forceinline__ u64 mkf(float v, uint32_t tag) { return mk(__float_as_uint(v), tag); }
__device__ __forceinline__ void st_tag1(u64* p, u64 a) { asm volatile("st.relaxed.gpu.global.b64 [%0], %1;" ::"l"(p), "l"(a) : "memory"); }
__device__ __forceinline__ void st_tag2(u64* p, u64 a, u64 b) { asm volatile("st.relaxed.gpu.global.v2.b64 [%0], {%1,%2};" ::"l"(p), "l"(a), "l"(b) : "memory"); }
__device__ __forceinline__ void ld_tag2(const u64* p, u64& a, u64& b) { asm volatile("ld.relaxed.gpu.global.v2.b64 {%0,%1}, [%2];" : "=l"(a), "=l"(b) : "l"(p) : "memory"); }
__device__ __forceinline__ bool tag_ok(u64 a, u64 b, uint32_t tag) { return ((((uint32_t)(a >> 32) ^ tag) | ((uint32_t)(b >> 32) ^ tag)) & 0xffffu) == 0u; }
__device__ __forceinline__ void spin_clks(int n) { const long long c = clock64(); while (clock64() - c < n) {} }
#define MLA_BACKOFF 0
#define MLA_DELAY 400
__device__ __forceinline__ float lo_f(u64 a) { return __uint_as_float((uint32_t)a); }

__device__ __forceinline__ uint32_t pack_bf16(float lo, float hi) {
    __nv_bfloat162 v = __floats2bfloat162_rn(lo, hi);
    return *reinterpret_cast<uint32_t*>(&v);
}
__device__ __forceinline__ float bf_lo(uint32_t w) { return __uint_as_float(w << 16); }
__device__ __forceinline__ float bf_hi(uint32_t w) { return __uint_as_float(w & 0xffff0000u); }
__device__ __forceinline__ void split2(float a, float b, uint32_t& hi, uint32_t& lo) {
    hi = pack_bf16(a, b);
    lo = pack_bf16(a - bf_lo(hi), b - bf_hi(hi));
}
__device__ __forceinline__ float wsum(float v) {
#pragma unroll
    for (int o = 16; o > 0; o >>= 1) v += __shfl_xor_sync(0xffffffffu, v, o);
    return v;
}

template <int N, int stride, bool init = true>
__device__ __forceinline__ void poll_pairs(const u64* base, int n, u64 (&a)[N], u64 (&b)[N], uint32_t tag) {
    const u64 ok = (u64)tag << 32;
    if (init) {
#pragma unroll
        for (int i = 0; i < N; i++) { a[i] = i < n ? 0ull : ok; b[i] = a[i]; }
    }
    int lim = 0;
    while (true) {
#pragma unroll
        for (int i = 0; i < N; i++) if (!tag_ok(a[i], b[i], tag)) ld_tag2(base + i * stride, a[i], b[i]);
        bool all = true;
#pragma unroll
        for (int i = 0; i < N; i++) all = all && tag_ok(a[i], b[i], tag);
        if (__all_sync(0xffffffffu, all) || ++lim > SPIN_LIMIT) break;
    }
}
#define TSTAMP(i) do {} while (0)

template <int CL> struct SM {
    static constexpr int W = DC_ / CL;
    static constexpr int QA_PITCH = W * 2 + 16;
    static constexpr int VBD_PITCH = MAXUB * 32 + 16;
    static constexpr int RING = 0;
    static constexpr int BARS = NSLOT * 8192;
    static constexpr int PART = BARS + 768;
    static constexpr int PBUF = PART + 16384;
    static constexpr int PML = PBUF + MAXCH * CL * 512;
    static constexpr int QA = PML + MAXCH * CL * 128;
    static constexpr int VBQ = QA + 16 * QA_PITCH;
    static constexpr int VBD = VBQ + 4 * 528;
    static constexpr int VBE = VBD + 4 * VBD_PITCH;
    static constexpr int VBF = VBE + 2 * 144;
    static constexpr int FAC = VBF + 2 * 928;
    static constexpr int RED = FAC + 2 * MAXNC * 4;
    static constexpr int STAT = RED + 8 * 64 * 4;
    static constexpr int XS = STAT + 128;
    static constexpr int TAB = XS + 896;
    static constexpr int RS = TAB + 512;
    static constexpr int END = RS + 4096;
};
enum { B_FULL = 0, B_REL = MAXGR, B_PART = B_REL + 7, B_P = B_PART + MAXCH, B_Q = B_P + MAXCH, B_QA, B_FAC, B_E, B_F2, B_X,
       GO_Q, GO_QA, B_RS1, GO_CTX, B_RS2, B_COUNT };
static_assert(B_COUNT <= 96, "barrier area");

template <int CL>
__global__ void __launch_bounds__(NTHREADS, 1)
mla_kernel(const __grid_constant__ Maps TM, const __grid_constant__ Params P) {
    typedef SM<CL> S;
    constexpr int W = S::W;
    constexpr int SL = 8 / CL;
    constexpr int NP = W / 128;
    constexpr int KPG = CL * 4;
    constexpr int TPG = KPG / 16;
    extern __shared__ unsigned char smem_raw[];
    const uint32_t sb = (smem_u32(smem_raw) + 1023u) & ~1023u;
    unsigned char* const sp = smem_raw + (sb - smem_u32(smem_raw));
    const int tid = threadIdx.x, warp = tid >> 5, lane = tid & 31;
    const int g = lane >> 2, t = lane & 3;
    const int b = blockIdx.x, G = P.G, NC = P.NC;
    const int rank = b % CL, cid = b / CL;
    auto BAR = [&](int i) { return sb + S::BARS + 8u * i; };
    auto SLOTI = [&](int gr) { return gr >= 2 * NSLOT ? gr - 2 * NSLOT : (gr >= NSLOT ? gr - NSLOT : gr); };
    auto SLOT = [&](int gr) { return sb + S::RING + (uint32_t)SLOTI(gr) * 8192u; };
    auto WAITG = [&](int gr) { mbar_wait(BAR(B_FULL + gr)); };

    const int uB0 = b * P.qB + min(max(b - P.lB, 0), P.rB), nB = P.qB + (b >= P.lB && b < P.lB + P.rB);
    const int h1 = uB0 >> 6, h2 = (uB0 + nB - 1) >> 6;
    const int uE0 = b * P.qE + min(max(b - P.lE, 0), P.rE), nE = P.qE + (b >= P.lE && b < P.lE + P.rE);
    const int nKG = P.qK + (cid < P.rK);
    const int T = nKG * TPG;
    const int NCH = (nKG + 3) >> 2;
    const bool isF = b < NFCTA;
    const int G_UK = nE, G_C = G_UK + nB, G_UV = G_C + nKG, G_WO = G_UV + nB, G_FG = G_WO + nE, G_WD = G_FG + 4, NGR = isF ? G_WD + 2 : G_FG;

    TSTAMP(0);
    if (warp == 9) {
        if (lane == 0) {
            prefetch_tm(&TM.m[0]); prefetch_tm(&TM.m[2]);
#pragma unroll
            for (int i = 0; i < NINIT; i++) mbar_init(BAR(B_FULL + i), 1);
            mbar_init(BAR(B_X), 1);
            asm volatile("fence.mbarrier_init.release.cluster;" ::: "memory");
            asm volatile("fence.proxy.async.shared::cta;" ::: "memory");
            mbar_expect_tx(BAR(B_X), 896);
            asm volatile("cp.async.bulk.shared::cluster.global.mbarrier::complete_tx::bytes [%0], [%1], %2, [%3];" ::"r"(sb + S::XS), "l"(P.x), "r"(896), "r"(BAR(B_X)) : "memory");
#pragma unroll
            for (int i = 0; i < NINIT; i++) {
                if (i < 4 || i < nE) {
                    mbar_expect_tx(BAR(B_FULL + i), 7168);
                    tma4d(sb + S::RING + i * 8192, &TM.m[0], ((uE0 + i) >> 1) * 16, ((uE0 + i) & 1) * 224, 0, 0, BAR(B_FULL + i));
                } else {
                    const int u = uB0 + i - nE;
                    mbar_expect_tx(BAR(B_FULL + i), 8192);
                    tma4d(sb + S::RING + i * 8192, &TM.m[2], 0, (u & 63) * 16, 0, u >> 6, BAR(B_FULL + i));
                }
            }
        }
        if (lane == 1) {
#pragma unroll
            for (int i = 1; i < 8; i++) prefetch_tm(&TM.m[i]);
        }
        __syncwarp();
        TSTAMP(22);
        __syncthreads();
        asm volatile("barrier.cluster.arrive.relaxed.aligned;" ::: "memory");
        {
            const uint32_t m0 = (lds32(sb + S::TAB + lane * 8 + 4) >> 16) & 255, m1 = (lds32(sb + S::TAB + lane * 8 + 260) >> 16) & 255;
            if (lane >= NINIT) mbar_expect_tx(BAR(B_FULL + lane), (m0 >= 1 && m0 <= 3) ? 8192 : 7168);
            if (lane + 32 < NGR) mbar_expect_tx(BAR(B_FULL + lane + 32), (m1 >= 1 && m1 <= 3) ? 8192 : 7168);
        }
        __syncwarp();
        TSTAMP(17);
        int next = NINIT, mine = lane < NINIT ? lane : -1, rel_ok = 0, lim = 0;
#pragma unroll 1
        while (next < NGR && ++lim < (SPIN_LIMIT << 6)) {
            const int wflag = *reinterpret_cast<volatile int*>(sp + S::STAT + 16);
            const int win = next >= G_WO ? MLA_WIND : wflag;
            const bool fin = mine < 0 || mbar_test(BAR(B_FULL + mine));
            if (fin) mine = -1;
            const unsigned busy = __ballot_sync(0xffffffffu, !fin);
            if (__popc(busy) >= win) continue;
            const uint2 e = *reinterpret_cast<const uint2*>(sp + S::TAB + next * 8);
            const int need = e.y >> 24;
            if (need > rel_ok) { if (!mbar_test(BAR(B_REL + need - 1))) continue; rel_ok = need; }
            if (lane == __ffs(~busy) - 1) {
                tma4d(SLOT(next), &TM.m[(e.y >> 16) & 255], e.x & 0xffff, e.x >> 16, e.y & 255, (e.y >> 8) & 255, BAR(B_FULL + next));
                mine = next;
            }
            __syncwarp();
            next++;
        }
        TSTAMP(18);
        cluster_wait();
        return;
    }

    if (tid == 0) {
#pragma unroll
        for (int i = NINIT; i < 30; i++) mbar_init(BAR(B_FULL + i), 1);
        asm volatile("fence.mbarrier_init.release.cluster;" ::: "memory");
        asm volatile("fence.proxy.async.shared::cta;" ::: "memory");
    } else if (tid == 64) {
#pragma unroll
        for (int i = 30; i < B_REL; i++) mbar_init(BAR(B_FULL + i), 1);
        asm volatile("fence.mbarrier_init.release.cluster;" ::: "memory");
        asm volatile("fence.proxy.async.shared::cta;" ::: "memory");
    } else if (tid == 320) {
#pragma unroll
        for (int i = B_REL; i < B_PART; i++) mbar_init(BAR(i), 8);
#pragma unroll
        for (int i = B_PART; i < B_Q; i++) mbar_init(BAR(i), 1);
        asm volatile("fence.mbarrier_init.release.cluster;" ::: "memory");
    } else if (tid == 352) {
#pragma unroll
        for (int i = B_Q; i < B_COUNT; i++) if (i != B_X) mbar_init(BAR(i), 1);
        asm volatile("fence.mbarrier_init.release.cluster;" ::: "memory");
    }
    uint32_t tag;
    {
        const unsigned* ep;
        asm volatile("mov.u64 %0, %1;" : "=l"(ep) : "l"(g_s + O_EPOCH));
        asm volatile("ld.relaxed.gpu.global.u32 %0, [%1];" : "=r"(tag) : "l"(ep) : "memory");
    }
    if (warp == 1) {
            if (lane == 0) *reinterpret_cast<volatile int*>(sp + S::STAT + 16) = WIN;
#pragma unroll
            for (int k = 0; k < 2; k++) {
                const int gr = lane + 32 * k;
                int c0 = 0, c1, c2 = 0, c3 = 0, mp;
                if (gr < G_UK) { const int u = uE0 + gr; mp = 0; c0 = (u >> 1) * 16; c1 = (u & 1) * 224; }
                else if (gr < G_C) { const int u = uB0 + gr - G_UK; mp = 2; c1 = (u & 63) * 16; c3 = u >> 6; }
                else if (gr < G_UV) { mp = 1; c1 = ((gr - G_C) * NC + cid) * KPG; c2 = rank * (W / 64); }
                else if (gr < G_WO) { const int u = uB0 + gr - G_UV; mp = 3; c1 = (u & 63) * 16; c3 = u >> 6; }
                else if (gr < G_FG) { mp = 4; c1 = (uE0 + gr - G_WO) * 8; }
                else if (gr < G_WD) { const int i = gr - G_FG; mp = 5 + (i >> 1); c0 = b * 16; c1 = (i & 1) * 224; }
                else { mp = 7; c1 = b * 16 + (gr - G_WD) * 8; }
                const int pg = gr - NSLOT;
                const int rl = pg < 0 ? -1 : (pg < G_C ? 0 : (pg < G_UV ? 1 + ((pg - G_C) >> 2) : 6));
                *reinterpret_cast<uint2*>(sp + S::TAB + gr * 8) = make_uint2((uint32_t)c0 | ((uint32_t)c1 << 16), (uint32_t)c2 | ((uint32_t)c3 << 8) | ((uint32_t)mp << 16) | ((uint32_t)(rl + 1) << 24));
            }
    } else if (warp == 8) {
        for (int i = lane; i < nE * 8; i += 32) { const int u = uE0 + (i >> 3); st_tag2(GS(O_Q + (u & 1) * (H_ * D_) + (u >> 1) * 16 + (i & 7) * 2), 0ull, 0ull); }
        for (int i = lane; i < nB * 4; i += 32) st_tag2(GS(O_QA + uB0 * 8 + i * 2), 0ull, 0ull);
    }
    __syncthreads();
    asm volatile("barrier.cluster.arrive.relaxed.aligned;" ::: "memory");
    asm volatile("" : "+r"(tag));
    tag += 1u;

    if (warp == 8) {
        uint32_t rpb[CL];
#pragma unroll
        for (int dst = 0; dst < CL; dst++) rpb[dst] = mapa(sb, dst);
        const uint32_t rml0 = mapa(sb, t % CL), rml1 = mapa(sb, (t + 4) % CL);
        if (lane < NCH) {
            const int nt = min(CL, T - lane * CL);
            if (lane * CL + rank < T) mbar_expect_tx(BAR(B_PART + lane), 8192);
            mbar_expect_tx(BAR(B_P + lane), nt * 640);
        }
        cluster_wait();
        mbar_wait(BAR(GO_Q));
        {
            u64* c1p = GS(O_CTX + ((b - P.firstB[h1]) * H_ + h1) * D_ + lane * 2);
            u64* c2p = GS(O_CTX + ((b - P.firstB[h2]) * H_ + h2) * D_ + lane * 2);
#pragma unroll
            for (int i = 0; i < 4; i++) { st_tag2(c1p + i * 64, 0ull, 0ull); st_tag2(c2p + i * 64, 0ull, 0ull); }
        }
        float Rlo = -INFINITY, Rhi = -INFINITY;
        for (int j = 0; j < NCH; j++) {
            if (j * CL + rank >= T) break;
            if (j > 0) {
                const int jp = j == 1 ? 0 : j - 2 + (j == 2);
                if (j != 2) {
                    mbar_wait(BAR(B_P + jp));
                    float nlo = -INFINITY, nhi = -INFINITY;
#pragma unroll
                    for (int tl = 0; tl < CL; tl++) {
                        const uint4 ml = lds128(sb + S::PML + (jp * CL + tl) * 128 + g * 16);
                        nlo = fmaxf(nlo, __uint_as_float(ml.x)); nhi = fmaxf(nhi, __uint_as_float(ml.z));
                    }
                    Rlo = nlo > Rlo + REF_SLACK ? nlo : Rlo; Rhi = nhi > Rhi + REF_SLACK ? nhi : Rhi;
                }
            }
            const uint32_t pa = sb + S::PART + (j & 1) * 8192 + lane * 16;
            const uint32_t opb = S::PBUF + (j * CL + rank) * 512 + lane * 16;
            const uint32_t opm = S::PML + (j * CL + rank) * 128 + g * 16;
            const uint32_t obar = S::BARS + 8 * (B_P + j);
            mbar_wait(BAR(B_PART + j));

            uint4 v0[8], v1[8];
#pragma unroll
            for (int src = 0; src < 8; src++) { v0[src] = lds128(pa + src * 1024); v1[src] = lds128(pa + src * 1024 + 512); }
#define SUM8(V, F) (((__uint_as_float(V[0].F) + __uint_as_float(V[1].F)) + (__uint_as_float(V[2].F) + __uint_as_float(V[3].F))) + \
                    ((__uint_as_float(V[4].F) + __uint_as_float(V[5].F)) + (__uint_as_float(V[6].F) + __uint_as_float(V[7].F))))
            const float s00 = SUM8(v0, x), s01 = SUM8(v0, y), s02 = SUM8(v0, z), s03 = SUM8(v0, w);
            const float s10 = SUM8(v1, x), s11 = SUM8(v1, y), s12 = SUM8(v1, z), s13 = SUM8(v1, w);
#undef SUM8

            float mlo = fmaxf(fmaxf(s00, s01), fmaxf(s10, s11));
            float mhi = fmaxf(fmaxf(s02, s03), fmaxf(s12, s13));
            mlo = fmaxf(mlo, __shfl_xor_sync(0xffffffffu, mlo, 1)); mhi = fmaxf(mhi, __shfl_xor_sync(0xffffffffu, mhi, 1));
            mlo = fmaxf(mlo, __shfl_xor_sync(0xffffffffu, mlo, 2)); mhi = fmaxf(mhi, __shfl_xor_sync(0xffffffffu, mhi, 2));

            mlo = mlo > Rlo + REF_SLACK ? mlo : Rlo; mhi = mhi > Rhi + REF_SLACK ? mhi : Rhi;
            const uint32_t a0 = pack_bf16(ex2(s00 - mlo), ex2(s01 - mlo));
            const uint32_t a1 = pack_bf16(ex2(s02 - mhi), ex2(s03 - mhi));
            const uint32_t a2 = pack_bf16(ex2(s10 - mlo), ex2(s11 - mlo));
            const uint32_t a3 = pack_bf16(ex2(s12 - mhi), ex2(s13 - mhi));
#pragma unroll
            for (int dst = 0; dst < CL; dst++) st_async_v4(rpb[dst] + opb, a0, a1, a2, a3, rpb[dst] + obar);

            float llo = (bf_lo(a0) + bf_hi(a0)) + (bf_lo(a2) + bf_hi(a2));
            float lhi = (bf_lo(a1) + bf_hi(a1)) + (bf_lo(a3) + bf_hi(a3));
            llo += __shfl_xor_sync(0xffffffffu, llo, 1); lhi += __shfl_xor_sync(0xffffffffu, lhi, 1);
            llo += __shfl_xor_sync(0xffffffffu, llo, 2); lhi += __shfl_xor_sync(0xffffffffu, lhi, 2);
            st_async_v4(rml0 + opm, __float_as_uint(mlo), __float_as_uint(llo), __float_as_uint(mhi), __float_as_uint(lhi), rml0 + obar);
            if (CL == 8) st_async_v4(rml1 + opm, __float_as_uint(mlo), __float_as_uint(llo), __float_as_uint(mhi), __float_as_uint(lhi), rml1 + obar);

        }
    } else if (warp == 10) {
        const int row = uE0 * 8 + lane * 2;
        const bool rowact = lane < nE * 4;
        const int ns = rowact ? P.nslot[row >> 8] : 0;
        const u64* cp = GS(O_CTX + (rowact ? row : 0));
        const int nq = h2 != h1 ? 8 : 4;
        cluster_wait();
        {
            mbar_wait(BAR(GO_Q)); spin_clks(MLA_DELAY);
            u64 a[8], bb[8], a2[8], b2[8];
            poll_pairs<8, 64>(GS(O_Q + h1 * D_ + lane * 2), nq, a, bb, tag);
            poll_pairs<8, 64>(GS(O_Q + H_ * D_ + h1 * D_ + lane * 2), nq, a2, b2, tag);
#pragma unroll
            for (int i = 0; i < 8; i++) {
                uint32_t hi, lo;
                const int o = S::VBQ + (i >> 2) * 2 * 528 + ((i & 3) * 32 + lane) * 4;
                split2(lo_f(a[i]) + lo_f(a2[i]), lo_f(bb[i]) + lo_f(b2[i]), hi, lo);
                *reinterpret_cast<uint32_t*>(sp + o) = hi; *reinterpret_cast<uint32_t*>(sp + o + 528) = lo;
            }
            __syncwarp();
            if (lane == 0) mbar_arrive(BAR(B_Q));
            TSTAMP(11);
        }
        {
            mbar_wait(BAR(GO_CTX)); spin_clks(MLA_DELAY);
            TSTAMP(56);
            u64 a[MAXSLOT], bb[MAXSLOT];
            poll_pairs<MAXSLOT, H_ * D_>(cp, ns, a, bb, tag);
            __syncwarp();
            TSTAMP(57);
            const float v0 = (((lo_f(a[0]) + lo_f(a[1])) + (lo_f(a[2]) + lo_f(a[3]))) + ((lo_f(a[4]) + lo_f(a[5])) + (lo_f(a[6]) + lo_f(a[7])))) + (lo_f(a[8]) + lo_f(a[9]));
            const float v1 = (((lo_f(bb[0]) + lo_f(bb[1])) + (lo_f(bb[2]) + lo_f(bb[3]))) + ((lo_f(bb[4]) + lo_f(bb[5])) + (lo_f(bb[6]) + lo_f(bb[7])))) + (lo_f(bb[8]) + lo_f(bb[9]));
            uint32_t hi, lo; split2(v0, v1, hi, lo);
            *reinterpret_cast<uint32_t*>(sp + S::VBE + lane * 4) = hi;
            *reinterpret_cast<uint32_t*>(sp + S::VBE + 144 + lane * 4) = lo;
            __syncwarp();
            if (lane == 0) mbar_arrive(BAR(B_E));
            TSTAMP(12);
        }
    } else if (warp == 11) {
        const int half = lane & 1;
        const bool own = rank < 7;
        const int col = (own ? rank * 64 : 0) + (lane >> 3) * 16 + (lane & 7);
        u64* x1d = GS(O_X1 + (rank * 16 + cid) * 64 + lane * 2);
        const u64* x1s = GS(O_X1 + ((cid * 8 + rank) * 16) * 64 + lane * 2);
        u64* x2d = GS(O_X2 + (rank * 16 + cid) * 64 + lane * 2);
        if (lane == 0) {
            if (own) { mbar_expect_tx(BAR(B_RS1), 2048); if (isF) mbar_expect_tx(BAR(B_RS2), 2048); }
            if (isF) { mbar_expect_tx(BAR(B_FAC), 7 * 256); mbar_expect_tx(BAR(B_F2), 7 * 8); }
        }
        mbar_wait(BAR(B_X));
        const float x0 = __bfloat162float(*reinterpret_cast<const __nv_bfloat16*>(sp + S::XS + col * 2));
        const float x1 = __bfloat162float(*reinterpret_cast<const __nv_bfloat16*>(sp + S::XS + col * 2 + 16));
        float piv = 0.f;
#pragma unroll
        for (int i = 0; i < 7; i++) { const uint32_t w = lds32(sb + S::XS + (i * 32 + lane) * 4); piv += bf_lo(w) + bf_hi(w); }
        piv = wsum(piv) * (1.f / M_);
        constexpr int NB = W / 128;
        const u64* qp = GS(O_QA + rank * (W / 2) + lane * 2);
        cluster_wait();
        {
            mbar_wait(BAR(GO_Q));
            if (own) {
                for (int c = 0; c < NC; c++) st_tag2(x1d + c * (8 * 16 * 64), 0ull, 0ull);
                st_tag2(x2d, 0ull, 0ull);
                if (cid == 0) st_tag2(GS(O_ACC + rank * 64 + lane * 2), 0ull, 0ull);
            }
            mbar_wait(BAR(GO_QA)); spin_clks(MLA_DELAY);
#pragma unroll
            for (int bt = 0; bt < NB; bt++) {
                u64 a[16], bb[16];
                poll_pairs<16, DC_ / 2>(qp + bt * 64, 16, a, bb, tag);
#pragma unroll
                for (int i = 0; i < 16; i++)
                    *reinterpret_cast<uint2*>(sp + S::QA + i * S::QA_PITCH + (bt * 32 + lane) * 8) = make_uint2((uint32_t)a[i], (uint32_t)bb[i]);
            }
            __syncwarp();
            if (lane == 0) { mbar_arrive(BAR(B_QA)); *reinterpret_cast<volatile int*>(sp + S::STAT + 16) = WINC; }
            TSTAMP(15);
        }
        if (own) {
            float hv0 = 0.f, hv1 = 0.f;
            {
                uint32_t rvb[CL];
#pragma unroll
                for (int d = 0; d < CL; d++) rvb[d] = mapa(sb, d);
                const uint32_t vo = S::VBF + (((rank * 4 + (lane >> 3)) * 4 + ((lane & 7) >> 1)) * 2 + half) * 8;
                mbar_wait(BAR(B_RS1));
                TSTAMP(52);
                float2 p[8];
#pragma unroll
                for (int i = 0; i < 8; i++) p[i] = *reinterpret_cast<const float2*>(sp + S::RS + i * 256 + lane * 8);
                const u64 w0 = mkf(((p[0].x + p[1].x) + (p[2].x + p[3].x)) + ((p[4].x + p[5].x) + (p[6].x + p[7].x)), tag);
                const u64 w1 = mkf(((p[0].y + p[1].y) + (p[2].y + p[3].y)) + ((p[4].y + p[5].y) + (p[6].y + p[7].y)), tag);
#pragma unroll
                for (int c = 0; c < NFCTA / CL; c++) st_tag2(x1d + c * (8 * 16 * 64), w0, w1);
                TSTAMP(53);
                if (isF) {
                    spin_clks(MLA_DELAY);
                    u64 a[16], bb[16];
                    poll_pairs<16, 64>(x1s, NC, a, bb, tag);
                    float v0 = 0.f, v1 = 0.f;
#pragma unroll
                    for (int i = 0; i < 16; i += 2) { v0 += lo_f(a[i]) + lo_f(a[i + 1]); v1 += lo_f(bb[i]) + lo_f(bb[i + 1]); }
                    hv0 = x0 + v0; hv1 = x1 + v1;
                    const float o0 = __shfl_xor_sync(0xffffffffu, hv0, 1), o1 = __shfl_xor_sync(0xffffffffu, hv1, 1);
                    uint32_t hiA, loA, hiB, loB;
                    split2((half ? o0 : hv0) - piv, (half ? hv0 : o0) - piv, hiA, loA);
                    split2((half ? o1 : hv1) - piv, (half ? hv1 : o1) - piv, hiB, loB);
#pragma unroll
                    for (int d = 0; d < CL; d++) st_async_v2(rvb[d] + vo, half ? loA : hiA, half ? loB : hiB, rvb[d] + S::BARS + 8 * B_FAC);
                    TSTAMP(13);
                    const float d0 = hv0 - piv, d1 = hv1 - piv;
                    float s1 = d0 + d1, s2 = d0 * d0 + d1 * d1;
#pragma unroll
                    for (int o = 16; o > 0; o >>= 1) { s1 += __shfl_xor_sync(0xffffffffu, s1, o); s2 += __shfl_xor_sync(0xffffffffu, s2, o); }
                    if (lane < CL) { const uint32_t rb = mapa(sb, lane); st_async_v2(rb + S::STAT + 64 + rank * 8, __float_as_uint(s1), __float_as_uint(s2), rb + S::BARS + 8 * B_F2); }
                }
            }
            if (isF) {
                mbar_wait(BAR(B_RS2));
                TSTAMP(54);
                float2 p[8];
#pragma unroll
                for (int i = 0; i < 8; i++) p[i] = *reinterpret_cast<const float2*>(sp + S::RS + 2048 + i * 256 + lane * 8);
                const float s0 = ((p[0].x + p[1].x) + (p[2].x + p[3].x)) + ((p[4].x + p[5].x) + (p[6].x + p[7].x));
                const float s1 = ((p[0].y + p[1].y) + (p[2].y + p[3].y)) + ((p[4].y + p[5].y) + (p[6].y + p[7].y));
                st_tag2(x2d, mkf(s0, tag), mkf(s1, tag));
                u64* ap = GS(O_ACC + rank * 64 + lane * 2);
                constexpr int NFC = NFCTA / CL;
                u64 enc[2], old[2];
#pragma unroll
                for (int k = 0; k < 2; k++) {
                    const float v = k ? s1 : s0;
                    enc[k] = (1ull << 60) + (1ull << 51) + (fabsf(v) < 2097152.f ? (u64)__float2ll_rn(v * 1073741824.f) : (1ull << 56));
                    asm volatile("atom.relaxed.gpu.global.add.u64 %0, [%1], %2;" : "=l"(old[k]) : "l"(ap + k), "l"(enc[k]) : "memory");
                }
                if (b == 0 && lane == 0) asm volatile("st.relaxed.gpu.global.u32 [%0], %1;" ::"l"(g_s + O_EPOCH), "r"(tag == 65535u ? 0u : tag) : "memory");
#pragma unroll
                for (int k = 0; k < 2; k++) {
                    const u64 tot = old[k] + enc[k];
                    if ((int)(tot >> 60) == NFC) {
                        float v;
                        if ((tot >> 56) & 15) {
                            v = 0.f;
                            for (int c = 0; c < NFC; c++) {
                                u64 a, bb; int lim = 0;
                                do { ld_tag2(GS(O_X2 + (rank * 16 + c) * 64 + lane * 2), a, bb); } while (!tag_ok(a, bb, tag) && ++lim < SPIN_LIMIT);
                                v += lo_f(k ? bb : a);
                            }
                        } else {
                            v = (float)((long long)(tot & ((1ull << 56) - 1)) - (long long)NFC * (1ll << 51)) * (1.f / 1073741824.f);
                        }
                        P.out[col + 8 * k] = __float2bfloat16((k ? hv1 : hv0) + v);
                        st_tag1(ap + k, 0ull);
                    }
                }
                TSTAMP(14);
            }
        }
    } else {
        const int mi = lane >> 3, r = lane & 7;
        if (warp < nE) {
            const int u = uE0 + warp;
            u64* dq = GS(O_Q + (u & 1) * (H_ * D_) + (u >> 1) * 16 + g);
            mbar_wait(BAR(B_X));
            uint32_t xw[7], bx[14][2];
#pragma unroll
            for (int i = 0; i < 7; i++) xw[i] = lds32(sb + S::XS + (i * 32 + lane) * 4);
#pragma unroll
            for (int ks = 0; ks < 14; ks++) {
                const uint32_t xa = sb + S::XS + ((u & 1) * 224 + ks * 16 + 2 * t) * 2;
                bx[ks][0] = lds32(xa); bx[ks][1] = lds32(xa + 16);
                if (g != 0) { bx[ks][0] = bx[ks][1] = g == 1 ? 0x3f803f80u : 0u; }
            }
            float s = 0.f;
#pragma unroll
            for (int i = 0; i < 7; i++) s += bf_lo(xw[i]) + bf_hi(xw[i]);
            const float mean = wsum(s) * (1.f / M_);
            float vs = 0.f;
#pragma unroll
            for (int i = 0; i < 7; i++) { const float d0 = bf_lo(xw[i]) - mean, d1 = bf_hi(xw[i]) - mean; vs += d0 * d0 + d1 * d1; }
            const float rstd = rsqrtf(wsum(vs) * (1.f / M_) + 1e-5f);
            float c[2][4];
#pragma unroll
            for (int i = 0; i < 2; i++) { c[i][0] = c[i][1] = c[i][2] = c[i][3] = 0.f; }
            const int rr = (mi >> 1) * 8 + r;
            const uint32_t wa = sb + S::RING + warp * 8192 + rr * 32 + ((((mi & 1) ^ (rr >> 2)) & 1) << 4);
            WAITG(warp);
#pragma unroll
            for (int ks = 0; ks < 14; ks++) {
                uint32_t a[4];
                ldsm4t(a, wa + ks * 512);
                mma16816(c[ks & 1], a, bx[ks][0], bx[ks][1]);
            }
            if (t == 0) {
                st_tag1(dq, mkf(((c[0][0] + c[1][0]) - mean * (c[0][1] + c[1][1])) * rstd, tag));
                st_tag1(dq + 8, mkf(((c[0][2] + c[1][2]) - mean * (c[0][3] + c[1][3])) * rstd, tag));
            }
            if (tid == 0) mbar_arrive(BAR(GO_Q));
            TSTAMP(1);
        }
        __syncwarp();
        cluster_wait();
        {
            mbar_wait(BAR(B_Q));
            uint32_t bq[16][2];
#pragma unroll
            for (int ks = 0; ks < 16; ks++) {
                bq[ks][0] = g < 4 ? lds32(sb + S::VBQ + g * 528 + (ks * 16 + 2 * t) * 2) : 0u;
                bq[ks][1] = g < 4 ? lds32(sb + S::VBQ + g * 528 + (ks * 16 + 2 * t + 8) * 2) : 0u;
            }
            TSTAMP(2);
            for (int un = warp; un < nB; un += 8) {
                WAITG(G_UK + un);
                const uint32_t rowa = sb + S::RING + (G_UK + un) * 8192 + ((mi & 1) * 8 + r) * 128;
                float c[4][4];
#pragma unroll
                for (int i = 0; i < 4; i++) { c[i][0] = c[i][1] = c[i][2] = c[i][3] = 0.f; }
#pragma unroll
                for (int ks = 0; ks < 16; ks++) {
                    uint32_t a[4];
                    const int ch = (ks & 3) * 2 + (mi >> 1);
                    ldsm4(a, rowa + (ks >> 2) * 2048 + ((ch ^ r) << 4));
                    mma16816(c[ks & 3], a, bq[ks][0], bq[ks][1]);
                }
                constexpr float SC = 0.0625f * 1.4426950408889634f;
                const float va = (((c[0][0] + c[1][0]) + (c[2][0] + c[3][0])) + ((c[0][1] + c[1][1]) + (c[2][1] + c[3][1]))) * SC;
                const float vb = (((c[0][2] + c[1][2]) + (c[2][2] + c[3][2])) + ((c[0][3] + c[1][3]) + (c[2][3] + c[3][3]))) * SC;
                const uint32_t wa = pack_bf16(va, __shfl_down_sync(0xffffffffu, va, 4));
                const uint32_t wb = pack_bf16(vb, __shfl_down_sync(0xffffffffu, vb, 4));
                const uint32_t wa2 = __shfl_down_sync(0xffffffffu, wa, 8), wb2 = __shfl_down_sync(0xffffffffu, wb, 8);
                const int u = uB0 + un;
                if (t == ((u >> 6) == h1 ? 0 : 1) && (g & 3) == 0) {
                    u64* dst = GS(O_QA + u * 8 + (g >> 1));
                    st_tag2(dst, mk(wa, tag), mk(wa2, tag));
                    st_tag2(dst + 4, mk(wb, tag), mk(wb2, tag));
                }
            }
            __syncwarp();
            if (lane == 0) mbar_arrive(BAR(B_REL + 0));
            if (tid == 0) { mbar_arrive(BAR(GO_QA)); *reinterpret_cast<volatile int*>(sp + S::STAT + 16) = WINB; }
            TSTAMP(3);

        }
        {
            const int tlw = warp / SL, sl = warp % SL;
            const uint32_t part_dst = mapa(sb + S::PART + (rank * SL + sl) * 1024 + lane * 16, tlw);
            const uint32_t part_bar = mapa(BAR(B_PART), tlw);
            const uint32_t sc_off = (sl * 2) * (KPG * 128) + ((tlw % TPG) * 16 + (mi >> 1) * 8 + r) * 128;
            const int cw = warp * (W / 8);
            const uint32_t pv_off = (cw >> 6) * (KPG * 128) + ((mi & 1) * 8 + r) * 128;
            mbar_wait(BAR(B_QA));
            uint32_t qa[8][4];
#pragma unroll
            for (int ks = 0; ks < 8; ks++) {
                const uint32_t a = sb + S::QA + g * S::QA_PITCH + (sl * 128 + ks * 16 + 2 * t) * 2;
                qa[ks][0] = lds32(a); qa[ks][1] = lds32(a + 8 * S::QA_PITCH); qa[ks][2] = lds32(a + 16); qa[ks][3] = lds32(a + 8 * S::QA_PITCH + 16);
            }
            float acc[NP * 2][4], acc2[NP * 2][4];
#pragma unroll
            for (int i = 0; i < NP * 2; i++) { acc[i][0] = acc[i][1] = acc[i][2] = acc[i][3] = 0.f; acc2[i][0] = acc2[i][1] = acc2[i][2] = acc2[i][3] = 0.f; }
            float Mlo = -INFINITY, Mhi = -INFINITY, Llo = 0.f, Lhi = 0.f;
            TSTAMP(4);
            {
                u64* gp = GS(O_PART + (cid * H_ + g) * (DC_ / 2) + (rank * W + warp * 16) / 2 + 2 * t);
                st_tag2(gp, 0ull, 0ull); st_tag2(gp + 8 * (DC_ / 2), 0ull, 0ull);
            }
            auto scores = [&](int j) {
                if (j * CL + tlw < T) {
                    const int gr = G_C + j * 4 + tlw / TPG;
                    const uint32_t rowa = SLOT(gr) + sc_off;
                    const uint32_t d = part_dst + (j & 1) * 8192, br = part_bar + 8 * j;
                    WAITG(gr);

                    float s[4][4];
#pragma unroll
                    for (int i = 0; i < 4; i++) { s[i][0] = s[i][1] = s[i][2] = s[i][3] = 0.f; }
#pragma unroll
                    for (int ks = 0; ks < 8; ks++) {
                        uint32_t bf[4];
                        const int ch = (ks & 3) * 2 + (mi & 1);
                        ldsm4(bf, rowa + (ks >> 2) * (KPG * 128) + ((ch ^ r) << 4));
                        mma16816(s[(ks & 1) * 2], qa[ks], bf[0], bf[1]);
                        mma16816(s[(ks & 1) * 2 + 1], qa[ks], bf[2], bf[3]);
                    }
                    st_async_v4(d, __float_as_uint(s[0][0] + s[2][0]), __float_as_uint(s[0][1] + s[2][1]), __float_as_uint(s[0][2] + s[2][2]), __float_as_uint(s[0][3] + s[2][3]), br);
                    st_async_v4(d + 512, __float_as_uint(s[1][0] + s[3][0]), __float_as_uint(s[1][1] + s[3][1]), __float_as_uint(s[1][2] + s[3][2]), __float_as_uint(s[1][3] + s[3][3]), br);
                    TSTAMP(24 + j);
                }
            };
#pragma unroll 1
            for (int j = -1; j < NCH; j++) {
                scores(j + 1);
                if (j < 0) continue;
                const int nt = min(CL, T - j * CL);
                const int g0 = G_C + j * 4;
                const uint32_t pml = sb + S::PML + j * CL * 128 + g * 16, ppb = sb + S::PBUF + j * CL * 512 + lane * 16;
                uint32_t va[4];
#pragma unroll
                for (int gi = 0; gi < 4; gi++) va[gi] = SLOT(g0 + (gi * TPG < nt ? gi : 0)) + pv_off;
                mbar_wait(BAR(B_P + j));
                TSTAMP(32 + j);
                uint4 ml[CL], pv[CL];
                uint32_t vf[CL][NP][4];
#pragma unroll
                for (int tl = 0; tl < CL; tl++) {
                    const int ts = tl < nt ? tl : 0;
                    pv[tl] = lds128(ppb + ts * 512);
#pragma unroll
                    for (int np = 0; np < NP; np++) {
                        const int ch = ((cw & 63) >> 3) + np * 2 + (mi >> 1);
                        ldsm4t(vf[tl][np], va[tl / TPG] + (tl % TPG) * 2048 + ((ch ^ r) << 4));
                    }
                    ml[tl] = lds128(pml + ts * 128);
                }
                bool stdref = true;
#pragma unroll
                for (int tl = 0; tl < CL; tl++) stdref = stdref && __uint_as_float(ml[tl].x) == Mlo && __uint_as_float(ml[tl].z) == Mhi;
                const bool fastp = __all_sync(0xffffffffu, stdref);

                if (fastp) {

#pragma unroll
                    for (int tl = 0; tl < CL; tl++) {
                        const bool on = tl < nt;
                        const uint32_t pa[4] = {on ? pv[tl].x : 0u, on ? pv[tl].y : 0u, on ? pv[tl].z : 0u, on ? pv[tl].w : 0u};
                        Llo += on ? __uint_as_float(ml[tl].y) : 0.f; Lhi += on ? __uint_as_float(ml[tl].w) : 0.f;
#pragma unroll
                        for (int np = 0; np < NP; np++) {
                            if (tl & 1) { mma16816(acc2[2 * np], pa, vf[tl][np][0], vf[tl][np][1]); mma16816(acc2[2 * np + 1], pa, vf[tl][np][2], vf[tl][np][3]); }
                            else { mma16816(acc[2 * np], pa, vf[tl][np][0], vf[tl][np][1]); mma16816(acc[2 * np + 1], pa, vf[tl][np][2], vf[tl][np][3]); }
                        }
                    }
                    if (lane == 0) mbar_arrive(BAR(B_REL + 1 + j));
                } else {
                    float nlo = Mlo, nhi = Mhi;
#pragma unroll
                    for (int tl = 0; tl < CL; tl++) {
                        if (tl >= nt) { ml[tl].x = 0xff800000u; ml[tl].z = 0xff800000u; }
                        nlo = fmaxf(nlo, __uint_as_float(ml[tl].x)); nhi = fmaxf(nhi, __uint_as_float(ml[tl].z));
                    }
                    nlo = nlo > Mlo + REF_SLACK ? nlo : Mlo; nhi = nhi > Mhi + REF_SLACK ? nhi : Mhi;
                    const float rlo = ex2(Mlo - nlo), rhi = ex2(Mhi - nhi);
                    Mlo = nlo; Mhi = nhi; Llo *= rlo; Lhi *= rhi;
#pragma unroll
                    for (int i = 0; i < NP * 2; i++) {
                        acc[i][0] = (acc[i][0] + acc2[i][0]) * rlo; acc[i][1] = (acc[i][1] + acc2[i][1]) * rlo;
                        acc[i][2] = (acc[i][2] + acc2[i][2]) * rhi; acc[i][3] = (acc[i][3] + acc2[i][3]) * rhi;
                        acc2[i][0] = acc2[i][1] = acc2[i][2] = acc2[i][3] = 0.f;
                    }
#pragma unroll
                    for (int tl = 0; tl < CL; tl++) {
                        const uint32_t pa[4] = {pv[tl].x, pv[tl].y, pv[tl].z, pv[tl].w};
                        const float flo = ex2(__uint_as_float(ml[tl].x) - Mlo), fhi = ex2(__uint_as_float(ml[tl].z) - Mhi);
                        Llo += flo * __uint_as_float(ml[tl].y); Lhi += fhi * __uint_as_float(ml[tl].w);
#pragma unroll
                        for (int np = 0; np < NP; np++) {
                            float t0[4] = {0.f, 0.f, 0.f, 0.f}, t1[4] = {0.f, 0.f, 0.f, 0.f};
                            mma16816(t0, pa, vf[tl][np][0], vf[tl][np][1]);
                            mma16816(t1, pa, vf[tl][np][2], vf[tl][np][3]);
                            acc[2 * np][0] += flo * t0[0]; acc[2 * np][1] += flo * t0[1]; acc[2 * np][2] += fhi * t0[2]; acc[2 * np][3] += fhi * t0[3];
                            acc[2 * np + 1][0] += flo * t1[0]; acc[2 * np + 1][1] += flo * t1[1]; acc[2 * np + 1][2] += fhi * t1[2]; acc[2 * np + 1][3] += fhi * t1[3];
                        }
                    }
                    if (lane == 0) mbar_arrive(BAR(B_REL + 1 + j));
                }
                TSTAMP(38 + j);
            }
            u64* gp = GS(O_PART + (cid * H_ + g) * (DC_ / 2) + (rank * W + warp * 16) / 2 + 2 * t);
            const float ilo = __fdividef(1.f, Llo), ihi = __fdividef(1.f, Lhi);
            const uint32_t wlo = __float_as_uint(Mlo + __log2f(Llo)), whi = __float_as_uint(Mhi + __log2f(Lhi));
            st_tag2(gp, mk(pack_bf16((acc[0][0] + acc2[0][0]) * ilo, (acc[0][1] + acc2[0][1]) * ilo), tag | (wlo & 0xffff0000u)),
                        mk(pack_bf16((acc[1][0] + acc2[1][0]) * ilo, (acc[1][1] + acc2[1][1]) * ilo), tag | (wlo << 16)));
            st_tag2(gp + 8 * (DC_ / 2), mk(pack_bf16((acc[0][2] + acc2[0][2]) * ihi, (acc[0][3] + acc2[0][3]) * ihi), tag | (whi & 0xffff0000u)),
                                        mk(pack_bf16((acc[1][2] + acc2[1][2]) * ihi, (acc[1][3] + acc2[1][3]) * ihi), tag | (whi << 16)));
            TSTAMP(5);
        }
        {
            uint32_t wa[MAXUB][2][4];
            const int d_it = tid >> 2, d_q = tid & 3;
            const bool d_act = d_it < nB * 4;
            const int d_u = uB0 + (d_it >> 2);
            const u64* d_ptr = GS(O_PART + d_q * (H_ * DC_ / 2) + (d_act ? d_u * 8 + (d_it & 3) * 2 : 0));
            const int d_n = d_act ? ((NC - d_q + 3) >> 2) : 0;
            const int hp = d_act && (d_u >> 6) != h1;
            u64 a[4], bb[4];
            {
                const uint32_t aoff = (warp >> 1) * 2048 + ((mi >> 1) * 8 + r) * 128;
                const int ch0 = (warp & 1) * 4 + (mi & 1);
#pragma unroll
                for (int ks = 0; ks < MAXUB; ks++) {
                    if (ks == MLA_DPOLL) {
#pragma unroll
                        for (int i = 0; i < 4; i++) { a[i] = bb[i] = (u64)tag << 32; if (i < d_n) ld_tag2(d_ptr + i * (4 * H_ * DC_ / 2), a[i], bb[i]); }
                    }
                    if (ks < nB) {
                        WAITG(G_UV + ks);
                        const uint32_t ua = SLOT(G_UV + ks) + aoff;
                        ldsm4t(wa[ks][0], ua + ((ch0 ^ r) << 4));
                        ldsm4t(wa[ks][1], ua + (((ch0 + 2) ^ r) << 4));
                    } else {
#pragma unroll
                        for (int k = 0; k < 4; k++) { wa[ks][0][k] = 0u; wa[ks][1][k] = 0u; }
                    }
                }
                __syncwarp();
                if (lane == 0) mbar_arrive(BAR(B_REL + 6));
            }
            TSTAMP(50);
            {
                poll_pairs<4, 4 * H_ * DC_ / 2, false>(d_ptr, d_n, a, bb, tag);
                float w[4], m = -INFINITY;
#pragma unroll
                for (int i = 0; i < 4; i++) {
                    w[i] = i < d_n ? __uint_as_float(((uint32_t)(a[i] >> 32) & 0xffff0000u) | (uint32_t)(bb[i] >> 48)) : -INFINITY;
                    m = fmaxf(m, w[i]);
                }
                m = fmaxf(m, __shfl_xor_sync(0xffffffffu, m, 1));
                m = fmaxf(m, __shfl_xor_sync(0xffffffffu, m, 2));
                if (!d_act) m = 0.f;
                float v0 = 0.f, v1 = 0.f, v2 = 0.f, v3 = 0.f, den = 0.f;
#pragma unroll
                for (int i = 0; i < 4; i++) {
                    const float e = ex2(w[i] - m);
                    den += e; v0 += e * bf_lo((uint32_t)a[i]); v1 += e * bf_hi((uint32_t)a[i]); v2 += e * bf_lo((uint32_t)bb[i]); v3 += e * bf_hi((uint32_t)bb[i]);
                }
#pragma unroll
                for (int o = 1; o < 4; o <<= 1) {
                    v0 += __shfl_xor_sync(0xffffffffu, v0, o); v1 += __shfl_xor_sync(0xffffffffu, v1, o); v2 += __shfl_xor_sync(0xffffffffu, v2, o);
                    v3 += __shfl_xor_sync(0xffffffffu, v3, o); den += __shfl_xor_sync(0xffffffffu, den, o);
                }
                if (d_it < MAXUB * 4) {
                    const float inv = __fdividef(1.f, den);
                    uint32_t hiA, loA, hiB, loB;
                    split2(v0 * inv, v1 * inv, hiA, loA); split2(v2 * inv, v3 * inv, hiB, loB);
                    const bool mine = d_act && hp == (d_q >> 1);
                    *reinterpret_cast<uint2*>(sp + S::VBD + (d_it * 4 + d_q) * 8) = mine ? ((d_q & 1) ? make_uint2(loA, loB) : make_uint2(hiA, hiB)) : make_uint2(0u, 0u);
                }
            }
            TSTAMP(6);
            const unsigned char* vb = sp + S::VBD + (t * 4 + (g & 3)) * 8;
            const int hh = t ? h2 : h1;
            u64* gc = GS(O_CTX + ((b - P.firstB[hh]) * H_ + hh) * D_ + warp * 32 + g);
            bar_compute();
            TSTAMP(51);
            float c[4][4];
#pragma unroll
            for (int i = 0; i < 4; i++) { c[i][0] = c[i][1] = c[i][2] = c[i][3] = 0.f; }
#pragma unroll
            for (int ks = 0; ks < MAXUB; ks++) {
                const uint2 bw = *reinterpret_cast<const uint2*>(vb + ks * 128);
                const uint32_t b0 = g < 4 ? bw.x : 0u, b1 = g < 4 ? bw.y : 0u;
                mma16816(c[(ks & 1) * 2], wa[ks][0], b0, b1);
                mma16816(c[(ks & 1) * 2 + 1], wa[ks][1], b0, b1);
            }
            if (t == 0 || (t == 1 && h2 != h1)) {
                st_tag1(gc, mkf((c[0][0] + c[2][0]) + (c[0][1] + c[2][1]), tag)); st_tag1(gc + 8, mkf((c[0][2] + c[2][2]) + (c[0][3] + c[2][3]), tag));
                st_tag1(gc + 16, mkf((c[1][0] + c[3][0]) + (c[1][1] + c[3][1]), tag)); st_tag1(gc + 24, mkf((c[1][2] + c[3][2]) + (c[1][3] + c[3][3]), tag));
            }
            if (tid == 0) mbar_arrive(BAR(GO_CTX));
            TSTAMP(7);
        }
        {
            uint32_t wa[4][3][4];
            uint32_t rsd[4];
#pragma unroll
            for (int i = 0; i < 4; i++) rsd[i] = mapa(sb, min((warp >> 2) + 2 * i, 6));
            const uint32_t rso = S::RS + rank * 256 + ((warp & 3) * 8 + g) * 8;
            const uint32_t vb = sb + S::VBE + (g & 1) * 144 + 4 * t;
#pragma unroll
            for (int ks = 0; ks < 3; ks++) {
                if (ks * 2 < nE) WAITG(G_WO + ks * 2);
                if (ks * 2 + 1 < nE) WAITG(G_WO + ks * 2 + 1);
                const uint32_t ua = SLOT(G_WO + min(ks * 2 + (mi >> 1), nE - 1)) + r * 128;
#pragma unroll
                for (int i = 0; i < 4; i++) {
                    const int mt = min(warp + 8 * i, 27);
                    const int ch = (mt & 3) * 2 + (mi & 1);
                    ldsm4t(wa[i][ks], ua + (mt >> 2) * 1024 + ((ch ^ r) << 4));
                }
            }
            mbar_wait(BAR(B_E));
            uint32_t bv[3][2];
#pragma unroll
            for (int ks = 0; ks < 3; ks++) {
                bv[ks][0] = lds32(vb + ks * 32); bv[ks][1] = lds32(vb + ks * 32 + 16);
                if (g >= 2) { bv[ks][0] = 0u; bv[ks][1] = 0u; }
            }
            float c[4][4];
#pragma unroll
            for (int i = 0; i < 4; i++) { c[i][0] = c[i][1] = c[i][2] = c[i][3] = 0.f; }
#pragma unroll
            for (int ks = 0; ks < 3; ks++)
#pragma unroll
                for (int i = 0; i < 4; i++) mma16816(c[i], wa[i][ks], bv[ks][0], bv[ks][1]);
#pragma unroll
            for (int i = 0; i < 4; i++)
                if (t == 0 && warp + 8 * i < 28) st_async_v2(rsd[i] + rso, __float_as_uint(c[i][0] + c[i][1]), __float_as_uint(c[i][2] + c[i][3]), rsd[i] + S::BARS + 8 * B_RS1);
            TSTAMP(8);
        }
        if (isF) {
            uint32_t wg[4][4], wu[4][4], wd[4][4];
            uint32_t rsd[4];
#pragma unroll
            for (int i = 0; i < 4; i++) rsd[i] = mapa(sb, min((warp >> 2) + 2 * i, 6));
            const uint32_t rso = S::RS + 2048 + rank * 256 + ((warp & 3) * 8 + g) * 8;
            const int nh = g < 2 ? (warp < 4 ? 4 : 3) : 0;
#pragma unroll
            for (int i = 0; i < 4; i++) WAITG(G_FG + i);
#pragma unroll
            for (int i = 0; i < 4; i++) {
                const int ks = min(warp + 8 * i, 27);
                const int row = ks * 16 + (mi >> 1) * 8 + r;
                const int hb = row >= 224, rr = row - hb * 224;
                const uint32_t o = rr * 32 + ((((mi & 1) ^ (rr >> 2)) & 1) << 4);
                ldsm4t(wg[i], SLOT(G_FG + hb) + o);
                ldsm4t(wu[i], SLOT(G_FG + 2 + hb) + o);
            }
            uint2 hf[4];
            mbar_wait(BAR(B_FAC));
#pragma unroll
            for (int i = 0; i < 4; i++) {
                hf[i] = *reinterpret_cast<const uint2*>(sp + S::VBF + (((warp + 8 * (i < nh ? i : 0)) * 4 + t) * 2 + (g & 1)) * 8);
                if (i >= nh) hf[i] = make_uint2(0u, 0u);
            }
            TSTAMP(19);
            float cg[2][4], cu[2][4];
#pragma unroll
            for (int i = 0; i < 2; i++) { cg[i][0] = cg[i][1] = cg[i][2] = cg[i][3] = 0.f; cu[i][0] = cu[i][1] = cu[i][2] = cu[i][3] = 0.f; }
#pragma unroll
            for (int i = 0; i < 4; i++) {
                uint32_t b0 = hf[i].x, b1 = hf[i].y;
                if (g == 2 && warp + 8 * i < 28) { b0 = b1 = 0x3f803f80u; }
                mma16816(cg[i & 1], wg[i], b0, b1);
                mma16816(cu[i & 1], wu[i], b0, b1);
            }
            float* red = reinterpret_cast<float*>(sp + S::RED);
            if (t < 2) {
                float* rp = red + warp * 64 + t * 32 + g;
                rp[0] = (cg[0][0] + cg[1][0]) + (cg[0][1] + cg[1][1]); rp[8] = (cg[0][2] + cg[1][2]) + (cg[0][3] + cg[1][3]);
                rp[16] = (cu[0][0] + cu[1][0]) + (cu[0][1] + cu[1][1]); rp[24] = (cu[0][2] + cu[1][2]) + (cu[0][3] + cu[1][3]);
            }
            WAITG(G_WD); WAITG(G_WD + 1);
#pragma unroll
            for (int i = 0; i < 4; i++) {
                const int mt = min(warp + 8 * i, 27);
                const int ch = (mt & 3) * 2 + (mi & 1);
                ldsm4t(wd[i], SLOT(G_WD + (mi >> 1)) + (mt >> 2) * 1024 + r * 128 + ((ch ^ r) << 4));
            }
            bar_compute();
            float rv[8], rc[8];
#pragma unroll
            for (int w = 0; w < 8; w++) { rv[w] = red[w * 64 + lane]; rc[w] = red[w * 64 + 32 + lane]; }
            TSTAMP(60);
            mbar_wait(BAR(B_F2));
            TSTAMP(61);
            float2 st;
            {
                float s1 = 0.f, s2 = 0.f;
#pragma unroll
                for (int i = 0; i < 7; i++) { const float2 p = *reinterpret_cast<const float2*>(sp + S::STAT + 64 + i * 8); s1 += p.x; s2 += p.y; }
                st.x = s1 * (1.f / M_);
                st.y = rsqrtf(fmaxf(s2 * (1.f / M_) - st.x * st.x, 0.f) + 1e-5f);
            }
            const float sv = ((rv[0] + rv[1]) + (rv[2] + rv[3])) + ((rv[4] + rv[5]) + (rv[6] + rv[7]));
            const float sc = ((rc[0] + rc[1]) + (rc[2] + rc[3])) + ((rc[4] + rc[5]) + (rc[6] + rc[7]));
            const float v = (sv - st.x * sc) * st.y;
            const float uu = __shfl_down_sync(0xffffffffu, v, 16);
            const float av = __fdividef(uu, 1.f + ex2(-1.4426950408889634f * v));
            const float a0 = __shfl_sync(0xffffffffu, av, 2 * t), a1 = __shfl_sync(0xffffffffu, av, 2 * t + 1);
            const float a2 = __shfl_sync(0xffffffffu, av, 2 * t + 8), a3 = __shfl_sync(0xffffffffu, av, 2 * t + 9);
            uint32_t h0, l0, h1b, l1b;
            split2(a0, a1, h0, l0); split2(a2, a3, h1b, l1b);
            const uint32_t b0 = g == 0 ? h0 : (g == 1 ? l0 : 0u), b1 = g == 0 ? h1b : (g == 1 ? l1b : 0u);
#pragma unroll
            for (int i = 0; i < 4; i++) {
                float c[4] = {0.f, 0.f, 0.f, 0.f};
                mma16816(c, wd[i], b0, b1);
                if (t == 0 && warp + 8 * i < 28) st_async_v2(rsd[i] + rso, __float_as_uint(c[0] + c[1]), __float_as_uint(c[2] + c[3]), rsd[i] + S::BARS + 8 * B_RS2);
            }
            TSTAMP(9);
        }
    }
}

typedef CUresult (*EncodeFn)(CUtensorMap*, CUtensorMapDataType, cuuint32_t, void*, const cuuint64_t*, const cuuint64_t*, const cuuint32_t*,
                             const cuuint32_t*, CUtensorMapInterleave, CUtensorMapSwizzle, CUtensorMapL2promotion, CUtensorMapFloatOOBfill);

struct HostState {
    bool ready;
    int CL;
    const void* ptrs[10];
    Maps tm;
    Params P;
    int smem;
};
HostState g_hs;

bool encode(EncodeFn fn, CUtensorMap* tm, const void* base, const cuuint64_t* dims, const cuuint64_t* strides, const cuuint32_t* box, CUtensorMapSwizzle sw) {
    cuuint32_t es[4] = {1, 1, 1, 1};
    return fn(tm, CU_TENSOR_MAP_DATA_TYPE_BFLOAT16, 4, const_cast<void*>(base), dims, strides, box, es, CU_TENSOR_MAP_INTERLEAVE_NONE, sw,
              CU_TENSOR_MAP_L2_PROMOTION_L2_128B, CU_TENSOR_MAP_FLOAT_OOB_FILL_NONE) == CUDA_SUCCESS;
}

bool plan(HostState& hs, int CL, int NC) {
    Params& P = hs.P;
    const int G = CL * NC;
    if (G < NFCTA || G > MAXG || NC > MAXNC) return false;
    P.G = G; P.NC = NC;
    P.qB = 1024 / G; P.rB = 1024 % G;
    P.qE = 512 / G; P.rE = 512 % G;
    P.lB = G - P.rB; P.lE = P.lB - P.rE > 0 ? P.lB - P.rE : 0;
    const int NKG = SK_ / (CL * 4);
    P.qK = NKG / NC; P.rK = NKG % NC;
    const int mB = P.qB + (P.rB > 0), mE = P.qE + (P.rE > 0), mK = P.qK + (P.rK > 0);
    if (mB > MAXUB || mE > 5 || (mK + 3) / 4 > MAXCH || 2 * mB + mK + 2 * mE + 6 > MAXGR || mE + mB > NSLOT || P.qE < 4) return false;
    for (int h = 0; h < H_; h++) {
        int first = -1, last = -1;
        for (int b = 0; b < G; b++) {
            const int u0 = b * P.qB + (b > P.lB ? b - P.lB : 0), u1 = u0 + P.qB + (b >= P.lB);
            if (u0 < 64 * (h + 1) && u1 > 64 * h) { if (first < 0) first = b; last = b; }
        }
        P.firstB[h] = (unsigned char)first; P.nslot[h] = (unsigned char)(last - first + 1);
        if (last - first + 1 > MAXSLOT) return false;
    }
    return true;
}

template <int CL> int max_clusters() {
    const int smem = SM<CL>::END + 1024;
    if (cudaFuncSetAttribute(mla_kernel<CL>, cudaFuncAttributeMaxDynamicSharedMemorySize, smem) != cudaSuccess) { cudaGetLastError(); return 0; }
    cudaLaunchConfig_t cfg = {};
    cfg.gridDim = dim3(CL * 16); cfg.blockDim = dim3(NTHREADS); cfg.dynamicSmemBytes = smem;
    cudaLaunchAttribute at[1];
    at[0].id = cudaLaunchAttributeClusterDimension; at[0].val.clusterDim.x = CL; at[0].val.clusterDim.y = 1; at[0].val.clusterDim.z = 1;
    cfg.attrs = at; cfg.numAttrs = 1;
    int n = 0;
    if (cudaOccupancyMaxActiveClusters(&n, mla_kernel<CL>, &cfg) != cudaSuccess) { cudaGetLastError(); return 0; }
    return n;
}

template <int CL> void launch(HostState& hs) {
    cudaLaunchConfig_t cfg = {};
    cfg.gridDim = dim3(hs.P.G); cfg.blockDim = dim3(NTHREADS); cfg.dynamicSmemBytes = hs.smem; cfg.stream = cudaStreamPerThread;
    cudaLaunchAttribute at[1];
    at[0].id = cudaLaunchAttributeClusterDimension; at[0].val.clusterDim.x = CL; at[0].val.clusterDim.y = 1; at[0].val.clusterDim.z = 1;
    cfg.attrs = at; cfg.numAttrs = 1;
    cudaLaunchKernelEx(&cfg, mla_kernel<CL>, hs.tm, hs.P);
}

#define MLA_FORCE_CL 0

void setup(HostState& hs, void* const* d_in, void* d_out) {
    EncodeFn fn = nullptr;
    cudaDriverEntryPointQueryResult qr;
    cudaGetDriverEntryPoint("cuTensorMapEncodeTiled", (void**)&fn, cudaEnableDefault, &qr);
    hs.CL = 0;
    const int cand[1] = {8};
    for (int i = 0; i < 1 && !hs.CL; i++) {
        const int CL = cand[i];
        if (MLA_FORCE_CL && CL != MLA_FORCE_CL) continue;
        int n = max_clusters<8>();
        if (n > MAXG / CL) n = MAXG / CL;
        if (plan(hs, CL, n)) { hs.CL = CL; hs.smem = SM<8>::END + 1024; }
    }
    {
        const cuuint32_t kpg = hs.CL * 4;
        cuuint64_t dims[4] = {64, SK_, 16, 1}, st[3] = {DC_ * 2, 128, 128}; cuuint32_t box[4] = {64, kpg, 64 / kpg, 1};
        encode(fn, &hs.tm.m[1], d_in[1], dims, st, box, CU_TENSOR_MAP_SWIZZLE_128B);
    }
    for (int i = 0; i < 2; i++) {
        cuuint64_t dims[4] = {64, DC_, 4, H_}, st[3] = {H_ * D_ * 2, 128, D_ * 2}; cuuint32_t box[4] = {64, 16, 4, 1};
        encode(fn, &hs.tm.m[2 + i], d_in[3 + i], dims, st, box, CU_TENSOR_MAP_SWIZZLE_128B);
    }
    {
        cuuint64_t dims[4] = {64, H_ * D_, 7, 1}, st[3] = {M_ * 2, 128, 128}; cuuint32_t box[4] = {64, 8, 7, 1};
        encode(fn, &hs.tm.m[4], d_in[5], dims, st, box, CU_TENSOR_MAP_SWIZZLE_128B);
    }
    for (int i = 0; i < 2; i++) {
        cuuint64_t dims[4] = {F_, M_, 1, 1}, st[3] = {F_ * 2, 128, 128}; cuuint32_t box[4] = {16, 224, 1, 1};
        encode(fn, &hs.tm.m[5 + i], d_in[7 + i], dims, st, box, CU_TENSOR_MAP_SWIZZLE_32B);
    }
    {
        cuuint64_t dims[4] = {64, F_, 7, 1}, st[3] = {M_ * 2, 128, 128}; cuuint32_t box[4] = {64, 8, 7, 1};
        encode(fn, &hs.tm.m[7], d_in[9], dims, st, box, CU_TENSOR_MAP_SWIZZLE_128B);
    }
    hs.P.x = (const __nv_bfloat16*)d_in[0];
    {
        cuuint64_t dims[4] = {H_ * D_, M_, 1, 1}, st[3] = {H_ * D_ * 2, 128, 128}; cuuint32_t box[4] = {16, 224, 1, 1};
        encode(fn, &hs.tm.m[0], d_in[2], dims, st, box, CU_TENSOR_MAP_SWIZZLE_32B);
    }
    hs.P.out = (__nv_bfloat16*)d_out;
    for (int i = 0; i < 10; i++) hs.ptrs[i] = d_in[i];
    hs.ready = true;
}

}

extern "C" void kernel_launch(void* const* d_in, const int* in_sizes, int n_in, void* d_out, int out_size) {
    HostState& hs = g_hs;
    bool same = hs.ready && hs.P.out == d_out;
    for (int i = 0; same && i < 10; i++) same = hs.ptrs[i] == d_in[i];
    if (!same) setup(hs, d_in, d_out);
    if (hs.CL == 8) launch<8>(hs);
}
```

```cpp
#include <cuda_runtime.h>
#include <cuda_bf16.h>
#include <cuda.h>
#include <stdint.h>

namespace {

constexpr int H_ = 16, SK_ = 8192, D_ = 256, M_ = 448, DC_ = 1024, F_ = 1792;
constexpr int NWARPS = 12;
constexpr int NTHREADS = NWARPS * 32;
constexpr int NFCTA = 112;
constexpr int MAXNC = 16;
constexpr int MAXG = 128;
constexpr int MAXCH = 5;
constexpr int MAXUB = 10;
constexpr int MAXSLOT = 10;
constexpr int NSLOT = 20;
constexpr int MAXGR = 56;
#define MLA_WIN 5
#define MLA_WINC 6
constexpr int WIN = MLA_WIN;
#define MLA_KPRE 10
#define MLA_WINB 4
constexpr int WINB = MLA_WINB;
#define MLA_WIND 3
constexpr int WINC = MLA_WINC;
#define MLA_NINIT 4
constexpr int NINIT = MLA_NINIT;
constexpr float REF_SLACK = 20.f;
constexpr int SPIN_LIMIT = 1 << 15;

typedef unsigned long long u64;

constexpr int O_Q = 0;
constexpr int O_QA = O_Q + 2 * H_ * D_;
constexpr int O_CTX = O_QA + H_ * DC_ / 2;
constexpr int O_X1 = O_CTX + MAXSLOT * H_ * D_;
constexpr int O_X2 = O_X1 + 8 * 16 * 64;
constexpr int O_ACC = O_X2 + 8 * 16 * 64;
constexpr int O_ACTX = O_ACC + 2 * 8 * 64;
constexpr int O_PART = O_ACTX + H_ * D_;
constexpr int O_EPOCH = O_PART + MAXNC * H_ * DC_ / 2;
__device__ __align__(128) u64 g_s[O_EPOCH + 16];

struct Params {
    const __nv_bfloat16* x;
    __nv_bfloat16* out;
    int G, NC;
    int qB, rB, lB;
    int qE, rE, lE;
    int qK, rK;
    unsigned char firstB[H_];
    unsigned char nslot[H_];
};

struct Maps { CUtensorMap m[8]; };

__device__ __forceinline__ uint32_t smem_u32(const void* p) { return (uint32_t)__cvta_generic_to_shared(p); }
__device__ __forceinline__ void mbar_init(uint32_t bar, int cnt) { asm volatile("mbarrier.init.shared::cta.b64 [%0], %1;" ::"r"(bar), "r"(cnt) : "memory"); }
__device__ __forceinline__ void mbar_expect_tx(uint32_t bar, uint32_t bytes) { asm volatile("mbarrier.arrive.expect_tx.shared::cta.b64 _, [%0], %1;" ::"r"(bar), "r"(bytes) : "memory"); }
__device__ __forceinline__ void mbar_arrive(uint32_t bar) { asm volatile("mbarrier.arrive.shared::cta.b64 _, [%0];" ::"r"(bar) : "memory"); }
__device__ __forceinline__ bool mbar_try(uint32_t bar, uint32_t parity) {
    uint32_t ok;
    asm volatile("{\n.reg .pred p;\nmbarrier.try_wait.parity.shared::cta.b64 p, [%1], %2;\nselp.b32 %0, 1, 0, p;\n}\n" : "=r"(ok) : "r"(bar), "r"(parity) : "memory");
    return ok != 0;
}
__device__ __forceinline__ bool mbar_test(uint32_t bar) {
    uint32_t ok;
    asm volatile("{\n.reg .pred p;\nmbarrier.test_wait.parity.shared::cta.b64 p, [%1], 0;\nselp.b32 %0, 1, 0, p;\n}\n" : "=r"(ok) : "r"(bar) : "memory");
    return ok != 0;
}
__device__ __forceinline__ void mbar_wait(uint32_t bar, uint32_t parity = 0) {
    if (__all_sync(0xffffffffu, mbar_try(bar, parity))) return;
    int lim = 0;
    while (!__all_sync(0xffffffffu, mbar_try(bar, parity)) && ++lim < SPIN_LIMIT) {}
}
__device__ __forceinline__ float ex2(float x) { float y; asm("ex2.approx.ftz.f32 %0, %1;" : "=f"(y) : "f"(x)); return y; }
__device__ __forceinline__ uint32_t mapa(uint32_t addr, uint32_t rank) {
    uint32_t r;
    asm volatile("mapa.shared::cluster.u32 %0, %1, %2;" : "=r"(r) : "r"(addr), "r"(rank));
    return r;
}
__device__ __forceinline__ void st_async_v4(uint32_t addr, uint32_t a, uint32_t b, uint32_t c, uint32_t d, uint32_t bar) {
    asm volatile("st.async.weak.shared::cluster.mbarrier::complete_tx::bytes.v4.b32 [%0], {%1,%2,%3,%4}, [%5];" ::"r"(addr), "r"(a), "r"(b), "r"(c), "r"(d), "r"(bar) : "memory");
}
__device__ __forceinline__ void st_async_v2(uint32_t addr, uint32_t a, uint32_t b, uint32_t bar) {
    asm volatile("st.async.weak.shared::cluster.mbarrier::complete_tx::bytes.v2.b32 [%0], {%1,%2}, [%3];" ::"r"(addr), "r"(a), "r"(b), "r"(bar) : "memory");
}
__device__ __forceinline__ void tma4d(uint32_t dst, const CUtensorMap* tm, int c0, int c1, int c2, int c3, uint32_t bar) {
    asm volatile("cp.async.bulk.tensor.4d.shared::cluster.global.mbarrier::complete_tx::bytes [%0], [%1, {%3, %4, %5, %6}], [%2];" ::"r"(dst), "l"(tm), "r"(bar), "r"(c0), "r"(c1), "r"(c2), "r"(c3) : "memory");
}
__device__ __forceinline__ void prefetch_tm(const CUtensorMap* tm) { asm volatile("prefetch.tensormap [%0];" ::"l"(tm) : "memory"); }
__device__ __forceinline__ void ldsm4(uint32_t (&r)[4], uint32_t addr) {
    asm volatile("ldmatrix.sync.aligned.m8n8.x4.shared.b16 {%0,%1,%2,%3}, [%4];" : "=r"(r[0]), "=r"(r[1]), "=r"(r[2]), "=r"(r[3]) : "r"(addr) : "memory");
}
__device__ __forceinline__ void ldsm4t(uint32_t (&r)[4], uint32_t addr) {
    asm volatile("ldmatrix.sync.aligned.m8n8.x4.trans.shared.b16 {%0,%1,%2,%3}, [%4];" : "=r"(r[0]), "=r"(r[1]), "=r"(r[2]), "=r"(r[3]) : "r"(addr) : "memory");
}
__device__ __forceinline__ void mma16816(float (&c)[4], const uint32_t (&a)[4], uint32_t b0, uint32_t b1) {
    asm volatile("mma.sync.aligned.m16n8k16.row.col.f32.bf16.bf16.f32 {%0,%1,%2,%3}, {%4,%5,%6,%7}, {%8,%9}, {%0,%1,%2,%3};"
                 : "+f"(c[0]), "+f"(c[1]), "+f"(c[2]), "+f"(c[3])
                 : "r"(a[0]), "r"(a[1]), "r"(a[2]), "r"(a[3]), "r"(b0), "r"(b1));
}
__device__ __forceinline__ uint32_t lds32(uint32_t addr) { uint32_t v; asm volatile("ld.shared.b32 %0, [%1];" : "=r"(v) : "r"(addr) : "memory"); return v; }
__device__ __forceinline__ uint4 lds128(uint32_t addr) { uint4 v; asm volatile("ld.shared.v4.b32 {%0,%1,%2,%3}, [%4];" : "=r"(v.x), "=r"(v.y), "=r"(v.z), "=r"(v.w) : "r"(addr) : "memory"); return v; }
__device__ __forceinline__ void bar_compute() { asm volatile("bar.sync 1, 256;" ::: "memory"); }
__device__ __forceinline__ void cluster_wait() { asm volatile("barrier.cluster.wait.acquire.aligned;" ::: "memory"); }

#define GS(off) (g_s + (uint32_t)(off))
__device__ __forceinline__ u64 mk(uint32_t payload, uint32_t tag) { return ((u64)tag << 32) | payload; }
__device__ __forceinline__ u64 mkf(float v, uint32_t tag) { return mk(__float_as_uint(v), tag); }
__device__ __forceinline__ void st_tag1(u64* p, u64 a) { asm volatile("st.relaxed.gpu.global.b64 [%0], %1;" ::"l"(p), "l"(a) : "memory"); }
__device__ __forceinline__ void st_tag2(u64* p, u64 a, u64 b) { asm volatile("st.relaxed.gpu.global.v2.b64 [%0], {%1,%2};" ::"l"(p), "l"(a), "l"(b) : "memory"); }
__device__ __forceinline__ void ld_tag2(const u64* p, u64& a, u64& b) { asm volatile("ld.relaxed.gpu.global.v2.b64 {%0,%1}, [%2];" : "=l"(a), "=l"(b) : "l"(p) : "memory"); }
__device__ __forceinline__ bool tag_ok(u64 a, u64 b, uint32_t tag) { return ((((uint32_t)(a >> 32) ^ tag) | ((uint32_t)(b >> 32) ^ tag)) & 0xffffu) == 0u; }
__device__ __forceinline__ void spin_clks(int n) { const long long c = clock64(); while (clock64() - c < n) {} }
#define MLA_DELAY 300
__device__ __forceinline__ float lo_f(u64 a) { return __uint_as_float((uint32_t)a); }

__device__ __forceinline__ u64 acc_enc(float v) {
    return (1ull << 59) + (1ull << 49) + (fabsf(v) < 33554432.f ? (u64)__float2ll_rn(v * 16777216.f) : (1ull << 54));
}
__device__ __forceinline__ int acc_cnt(u64 w) { return (int)(w >> 59); }
__device__ __forceinline__ bool acc_ovf(u64 w) { return ((w >> 54) & 31) != 0; }
__device__ __forceinline__ float acc_val(u64 w) { return (float)((long long)(w & ((1ull << 54) - 1)) - ((long long)(w >> 59) << 49)) * (1.f / 16777216.f); }
__device__ __forceinline__ void red_add(u64* p, u64 v) { asm volatile("red.relaxed.gpu.global.add.u64 [%0], %1;" ::"l"(p), "l"(v) : "memory"); }
__device__ __forceinline__ u64 atom_add(u64* p, u64 v) { u64 o; asm volatile("atom.relaxed.gpu.global.add.u64 %0, [%1], %2;" : "=l"(o) : "l"(p), "l"(v) : "memory"); return o; }
__device__ __forceinline__ void acc_wait(const u64* p, int n, u64& a, u64& b) {
    int lim = 0;
    while (!__all_sync(0xffffffffu, acc_cnt(a) == n && acc_cnt(b) == n) && ++lim < SPIN_LIMIT) { if (n > 0) ld_tag2(p, a, b); }
}

__device__ __forceinline__ uint32_t pack_bf16(float lo, float hi) {
    __nv_bfloat162 v = __floats2bfloat162_rn(lo, hi);
    return *reinterpret_cast<uint32_t*>(&v);
}
__device__ __forceinline__ float bf_lo(uint32_t w) { return __uint_as_float(w << 16); }
__device__ __forceinline__ float bf_hi(uint32_t w) { return __uint_as_float(w & 0xffff0000u); }
__device__ __forceinline__ void split2(float a, float b, uint32_t& hi, uint32_t& lo) {
    hi = pack_bf16(a, b);
    lo = pack_bf16(a - bf_lo(hi), b - bf_hi(hi));
}
__device__ __forceinline__ float wsum(float v) {
#pragma unroll
    for (int o = 16; o > 0; o >>= 1) v += __shfl_xor_sync(0xffffffffu, v, o);
    return v;
}

template <int N, int stride>
__device__ __forceinline__ void poll_pairs(const u64* base, int n, u64 (&a)[N], u64 (&b)[N], uint32_t tag) {
    const u64 ok = (u64)tag << 32;
#pragma unroll
    for (int i = 0; i < N; i++) { a[i] = i < n ? 0ull : ok; b[i] = a[i]; }
    int lim = 0;
    while (true) {
#pragma unroll
        for (int i = 0; i < N; i++) if (!tag_ok(a[i], b[i], tag)) ld_tag2(base + i * stride, a[i], b[i]);
        bool all = true;
#pragma unroll
        for (int i = 0; i < N; i++) all = all && tag_ok(a[i], b[i], tag);
        if (__all_sync(0xffffffffu, all) || ++lim > SPIN_LIMIT) break;
    }
}
#define TSTAMP(i) do {} while (0)
#define TSTAMP2(i) do {} while (0)

template <int CL> struct SM {
    static constexpr int W = DC_ / CL;
    static constexpr int QA_PITCH = W * 2 + 16;
    static constexpr int VBD_PITCH = MAXUB * 32 + 16;
    static constexpr int RING = 0;
    static constexpr int BARS = NSLOT * 8192;
    static constexpr int PART = BARS + 768;
    static constexpr int PBUF = PART + 16384;
    static constexpr int PML = PBUF + MAXCH * CL * 512;
    static constexpr int QA = PML + MAXCH * CL * 128;
    static constexpr int VBQ = QA + 16 * QA_PITCH;
    static constexpr int VBD = VBQ + 4 * 528;
    static constexpr int VBE = VBD + 4 * VBD_PITCH;
    static constexpr int VBF = VBE + 2 * 144;
    static constexpr int RED = VBF + 2 * 928;
    static constexpr int STAT = RED + 8 * 64 * 4;
    static constexpr int XS = STAT + 128;
    static constexpr int TAB = XS + 896;
    static constexpr int RS = TAB + 512;
    static constexpr int END = RS + 4096;
};
enum { B_FULL = 0, B_REL = MAXGR, B_PART = B_REL + 7, B_P = B_PART + MAXCH, B_Q = B_P + MAXCH, B_QA, B_FAC, B_E, B_F2, B_X,
       GO_Q, GO_QA, B_RS1, GO_CTX, B_RS2, GO_D, B_COUNT };
static_assert(B_COUNT <= 96, "barrier area");

template <int CL>
__global__ void __launch_bounds__(NTHREADS, 1)
mla_kernel(const __grid_constant__ Maps TM, const __grid_constant__ Params P) {
    typedef SM<CL> S;
    constexpr int W = S::W;
    constexpr int KPG = CL * 4;
    constexpr int TPG = KPG / 16;
    extern __shared__ unsigned char smem_raw[];
    const uint32_t sb = (smem_u32(smem_raw) + 1023u) & ~1023u;
    unsigned char* const sp = smem_raw + (sb - smem_u32(smem_raw));
    const int tid = threadIdx.x, warp = tid >> 5, lane = tid & 31;
    const int g = lane >> 2, t = lane & 3;
    const int b = blockIdx.x, NC = P.NC;
    const int rank = b % CL, cid = b / CL;
    auto BAR = [&](int i) { return sb + S::BARS + 8u * i; };
    auto SLOTI = [&](int gr) { return gr >= 2 * NSLOT ? gr - 2 * NSLOT : (gr >= NSLOT ? gr - NSLOT : gr); };
    auto SLOT = [&](int gr) { return sb + S::RING + (uint32_t)SLOTI(gr) * 8192u; };
    auto WAITG = [&](int gr) { mbar_wait(BAR(B_FULL + gr)); };

    const int uB0 = b * P.qB + min(max(b - P.lB, 0), P.rB), nB = P.qB + (b >= P.lB && b < P.lB + P.rB);
    const int h1 = uB0 >> 6, h2 = (uB0 + nB - 1) >> 6;
    const int uE0 = b * P.qE + min(max(b - P.lE, 0), P.rE), nE = P.qE + (b >= P.lE && b < P.lE + P.rE);
    const int nKG = P.qK + (cid < P.rK);
    const int T = nKG * TPG;
    const int NCH = (nKG + 3) >> 2;
    const bool isF = b < NFCTA;
    const int G_UK = nE, G_C = G_UK + nB, G_UV = G_C + nKG, G_WO = G_UV + nB, G_FG = G_WO + nE, G_WD = G_FG + 4, NGR = isF ? G_WD + 2 : G_FG;

    TSTAMP(0);
    if (warp == 9) {
        if (lane == 0) {
            prefetch_tm(&TM.m[0]); prefetch_tm(&TM.m[2]);
#pragma unroll
            for (int i = 0; i < NINIT; i++) mbar_init(BAR(B_FULL + i), 1);
            mbar_init(BAR(B_X), 1);
            asm volatile("fence.mbarrier_init.release.cluster;" ::: "memory");
            asm volatile("fence.proxy.async.shared::cta;" ::: "memory");
            mbar_expect_tx(BAR(B_X), 896);
            asm volatile("cp.async.bulk.shared::cluster.global.mbarrier::complete_tx::bytes [%0], [%1], %2, [%3];" ::"r"(sb + S::XS), "l"(P.x), "r"(896), "r"(BAR(B_X)) : "memory");
#pragma unroll
            for (int i = 0; i < NINIT; i++) {
                if (i < 4 || i < nE) {
                    mbar_expect_tx(BAR(B_FULL + i), 7168);
                    tma4d(sb + S::RING + i * 8192, &TM.m[0], ((uE0 + i) >> 1) * 16, ((uE0 + i) & 1) * 224, 0, 0, BAR(B_FULL + i));
                } else {
                    const int u = uB0 + i - nE;
                    mbar_expect_tx(BAR(B_FULL + i), 8192);
                    tma4d(sb + S::RING + i * 8192, &TM.m[2], 0, (u & 63) * 16, 0, u >> 6, BAR(B_FULL + i));
                }
            }
        }
        if (lane == 1) {
#pragma unroll
            for (int i = 1; i < 8; i++) prefetch_tm(&TM.m[i]);
        }
        __syncwarp();
        TSTAMP(22);
        __syncthreads();
        asm volatile("barrier.cluster.arrive.relaxed.aligned;" ::: "memory");
        {
            const uint32_t m0 = (lds32(sb + S::TAB + lane * 8 + 4) >> 16) & 255, m1 = (lds32(sb + S::TAB + lane * 8 + 260) >> 16) & 255;
            if (lane >= NINIT) mbar_expect_tx(BAR(B_FULL + lane), (m0 >= 1 && m0 <= 3) ? 8192 : 7168);
            if (lane + 32 < NGR) mbar_expect_tx(BAR(B_FULL + lane + 32), (m1 >= 1 && m1 <= 3) ? 8192 : 7168);
        }
        __syncwarp();
        TSTAMP(17);
        int next = NINIT, mine = lane < NINIT ? lane : -1, rel_ok = 0, lim = 0;
#pragma unroll 1
        while (next < NGR && ++lim < (SPIN_LIMIT << 6)) {
            const int wflag = *reinterpret_cast<volatile int*>(sp + S::STAT + 16);
            const int win = next >= G_WO ? MLA_WIND : wflag;
            const bool fin = mine < 0 || mbar_test(BAR(B_FULL + mine));
            if (fin) mine = -1;
            const unsigned busy = __ballot_sync(0xffffffffu, !fin);
            if (__popc(busy) >= win) continue;
            const uint2 e = *reinterpret_cast<const uint2*>(sp + S::TAB + next * 8);
            const int need = e.y >> 24;
            if (need > rel_ok) { if (!__all_sync(0xffffffffu, mbar_test(BAR(B_REL + need - 1)))) continue; rel_ok = need; }
            if (lane == __ffs(~busy) - 1) {
                tma4d(SLOT(next), &TM.m[(e.y >> 16) & 255], e.x & 0xffff, e.x >> 16, e.y & 255, (e.y >> 8) & 255, BAR(B_FULL + next));
                mine = next;
            }
            __syncwarp();
            next++;
        }
        TSTAMP(18);
        cluster_wait();
        return;
    }

    if (tid == 0) {
#pragma unroll
        for (int i = NINIT; i < 30; i++) mbar_init(BAR(B_FULL + i), 1);
        asm volatile("fence.mbarrier_init.release.cluster;" ::: "memory");
        asm volatile("fence.proxy.async.shared::cta;" ::: "memory");
    } else if (tid == 64) {
#pragma unroll
        for (int i = 30; i < B_REL; i++) mbar_init(BAR(B_FULL + i), 1);
        asm volatile("fence.mbarrier_init.release.cluster;" ::: "memory");
        asm volatile("fence.proxy.async.shared::cta;" ::: "memory");
    } else if (tid == 320) {
#pragma unroll
        for (int i = B_REL; i < B_PART; i++) mbar_init(BAR(i), 8);
#pragma unroll
        for (int i = B_PART; i < B_Q; i++) mbar_init(BAR(i), 1);
        asm volatile("fence.mbarrier_init.release.cluster;" ::: "memory");
    } else if (tid == 352) {
#pragma unroll
        for (int i = B_Q; i < B_COUNT; i++) if (i != B_X) mbar_init(BAR(i), 1);
        asm volatile("fence.mbarrier_init.release.cluster;" ::: "memory");
    }
    uint32_t tag;
    {
        const unsigned* ep;
        asm volatile("mov.u64 %0, %1;" : "=l"(ep) : "l"(g_s + O_EPOCH));
        asm volatile("ld.relaxed.gpu.global.u32 %0, [%1];" : "=r"(tag) : "l"(ep) : "memory");
    }
    if (warp == 1) {
            if (lane == 0) *reinterpret_cast<volatile int*>(sp + S::STAT + 16) = WIN;
#pragma unroll
            for (int k = 0; k < 2; k++) {
                const int gr = lane + 32 * k;
                int c0 = 0, c1, c2 = 0, c3 = 0, mp;
                if (gr < G_UK) { const int u = uE0 + gr; mp = 0; c0 = (u >> 1) * 16; c1 = (u & 1) * 224; }
                else if (gr < G_C) { const int u = uB0 + gr - G_UK; mp = 2; c1 = (u & 63) * 16; c3 = u >> 6; }
                else if (gr < G_UV) { mp = 1; c1 = ((gr - G_C) * NC + cid) * KPG; c2 = rank * (W / 64); }
                else if (gr < G_WO) { const int u = uB0 + gr - G_UV; mp = 3; c1 = (u & 63) * 16; c3 = u >> 6; }
                else if (gr < G_FG) { mp = 4; c1 = (uE0 + gr - G_WO) * 8; }
                else if (gr < G_WD) { const int i = gr - G_FG; mp = 5 + (i >> 1); c0 = b * 16; c1 = (i & 1) * 224; }
                else { mp = 7; c1 = b * 16 + (gr - G_WD) * 8; }
                const int pg = gr - NSLOT;
                const int rl = pg < 0 ? -1 : (pg < G_C ? 0 : (pg < G_UV ? 1 + ((pg - G_C) >> 2) : 6));
                *reinterpret_cast<uint2*>(sp + S::TAB + gr * 8) = make_uint2((uint32_t)c0 | ((uint32_t)c1 << 16), (uint32_t)c2 | ((uint32_t)c3 << 8) | ((uint32_t)mp << 16) | ((uint32_t)(rl + 1) << 24));
            }
    } else if (warp == 8) {
        for (int i = lane; i < nE * 8; i += 32) { const int u = uE0 + (i >> 3); st_tag2(GS(O_Q + (u & 1) * (H_ * D_) + (u >> 1) * 16 + (i & 7) * 2), 0ull, 0ull); }
        for (int i = lane; i < nB * 4; i += 32) st_tag2(GS(O_QA + uB0 * 8 + i * 2), 0ull, 0ull);
    }
    __syncthreads();
    asm volatile("barrier.cluster.arrive.relaxed.aligned;" ::: "memory");
    asm volatile("" : "+r"(tag));
    tag += 1u;

    auto recv_ctxl = [&](int th) {
        const int d_it = th >> 2, d_q = th & 3;
        const bool d_act = d_it < nB * 4;
        const int d_u = uB0 + (d_it >> 2);
        const u64* d_ptr = GS(O_PART + d_q * (H_ * DC_ / 2) + (d_act ? d_u * 8 + (d_it & 3) * 2 : 0));
        const int d_n = d_act ? ((NC - d_q + 3) >> 2) : 0;
        const int hp = d_act && (d_u >> 6) != h1;
        u64 a[4], bb[4];
        mbar_wait(BAR(GO_D));
        spin_clks(MLA_DELAY);
        poll_pairs<4, 4 * H_ * DC_ / 2>(d_ptr, d_n, a, bb, tag);
        float w[4], m = -INFINITY;
#pragma unroll
        for (int i = 0; i < 4; i++) {
            w[i] = i < d_n ? __uint_as_float(((uint32_t)(a[i] >> 32) & 0xffff0000u) | (uint32_t)(bb[i] >> 48)) : -INFINITY;
            m = fmaxf(m, w[i]);
        }
        m = fmaxf(m, __shfl_xor_sync(0xffffffffu, m, 1));
        m = fmaxf(m, __shfl_xor_sync(0xffffffffu, m, 2));
        if (!d_act) m = 0.f;
        float v0 = 0.f, v1 = 0.f, v2 = 0.f, v3 = 0.f, den = 0.f;
#pragma unroll
        for (int i = 0; i < 4; i++) {
            const float e = ex2(w[i] - m);
            den += e; v0 += e * bf_lo((uint32_t)a[i]); v1 += e * bf_hi((uint32_t)a[i]); v2 += e * bf_lo((uint32_t)bb[i]); v3 += e * bf_hi((uint32_t)bb[i]);
        }
#pragma unroll
        for (int o = 1; o < 4; o <<= 1) {
            v0 += __shfl_xor_sync(0xffffffffu, v0, o); v1 += __shfl_xor_sync(0xffffffffu, v1, o); v2 += __shfl_xor_sync(0xffffffffu, v2, o);
            v3 += __shfl_xor_sync(0xffffffffu, v3, o); den += __shfl_xor_sync(0xffffffffu, den, o);
        }
        const float inv = __fdividef(1.f, den);
        uint32_t hiA, loA, hiB, loB;
        split2(v0 * inv, v1 * inv, hiA, loA); split2(v2 * inv, v3 * inv, hiB, loB);
        const bool mine = d_act && hp == (d_q >> 1);
        *reinterpret_cast<uint2*>(sp + S::VBD + (d_it * 4 + d_q) * 8) = mine ? ((d_q & 1) ? make_uint2(loA, loB) : make_uint2(hiA, hiB)) : make_uint2(0u, 0u);
    };

    if (warp == 8) {
        uint32_t rpb[CL];
#pragma unroll
        for (int dst = 0; dst < CL; dst++) rpb[dst] = mapa(sb, dst);
        const uint32_t rml0 = mapa(sb, t % CL), rml1 = mapa(sb, (t + 4) % CL);
        if (lane < NCH) {
            const int nt = min(CL, T - lane * CL);
            if (lane * CL + rank < T) mbar_expect_tx(BAR(B_PART + lane), 8192);
            mbar_expect_tx(BAR(B_P + lane), nt * 640);
        }
        cluster_wait();
        float Rlo = -INFINITY, Rhi = -INFINITY;
        for (int j = 0; j < NCH; j++) {
            if (j * CL + rank >= T) break;
            if (j > 0) {
                const int jp = j == 1 ? 0 : j - 2 + (j == 2);
                if (j != 2) {
                    mbar_wait(BAR(B_P + jp));
                    float nlo = -INFINITY, nhi = -INFINITY;
#pragma unroll
                    for (int tl = 0; tl < CL; tl++) {
                        const uint4 ml = lds128(sb + S::PML + (jp * CL + tl) * 128 + g * 16);
                        nlo = fmaxf(nlo, __uint_as_float(ml.x)); nhi = fmaxf(nhi, __uint_as_float(ml.z));
                    }
                    Rlo = nlo > Rlo + REF_SLACK ? nlo : Rlo; Rhi = nhi > Rhi + REF_SLACK ? nhi : Rhi;
                }
            }
            const uint32_t pa = sb + S::PART + (j & 1) * 8192 + lane * 16;
            const uint32_t opb = S::PBUF + (j * CL + rank) * 512 + lane * 16;
            const uint32_t opm = S::PML + (j * CL + rank) * 128 + g * 16;
            const uint32_t obar = S::BARS + 8 * (B_P + j);
            mbar_wait(BAR(B_PART + j));

            uint4 v0[8], v1[8];
#pragma unroll
            for (int src = 0; src < 8; src++) { v0[src] = lds128(pa + src * 1024); v1[src] = lds128(pa + src * 1024 + 512); }
#define SUM8(V, F) (((__uint_as_float(V[0].F) + __uint_as_float(V[1].F)) + (__uint_as_float(V[2].F) + __uint_as_float(V[3].F))) + \
                    ((__uint_as_float(V[4].F) + __uint_as_float(V[5].F)) + (__uint_as_float(V[6].F) + __uint_as_float(V[7].F))))
            const float s00 = SUM8(v0, x), s01 = SUM8(v0, y), s02 = SUM8(v0, z), s03 = SUM8(v0, w);
            const float s10 = SUM8(v1, x), s11 = SUM8(v1, y), s12 = SUM8(v1, z), s13 = SUM8(v1, w);
#undef SUM8

            float mlo = fmaxf(fmaxf(s00, s01), fmaxf(s10, s11));
            float mhi = fmaxf(fmaxf(s02, s03), fmaxf(s12, s13));
            mlo = fmaxf(mlo, __shfl_xor_sync(0xffffffffu, mlo, 1)); mhi = fmaxf(mhi, __shfl_xor_sync(0xffffffffu, mhi, 1));
            mlo = fmaxf(mlo, __shfl_xor_sync(0xffffffffu, mlo, 2)); mhi = fmaxf(mhi, __shfl_xor_sync(0xffffffffu, mhi, 2));

            mlo = mlo > Rlo + REF_SLACK ? mlo : Rlo; mhi = mhi > Rhi + REF_SLACK ? mhi : Rhi;
            const uint32_t a0 = pack_bf16(ex2(s00 - mlo), ex2(s01 - mlo));
            const uint32_t a1 = pack_bf16(ex2(s02 - mhi), ex2(s03 - mhi));
            const uint32_t a2 = pack_bf16(ex2(s10 - mlo), ex2(s11 - mlo));
            const uint32_t a3 = pack_bf16(ex2(s12 - mhi), ex2(s13 - mhi));
#pragma unroll
            for (int dst = 0; dst < CL; dst++) st_async_v4(rpb[dst] + opb, a0, a1, a2, a3, rpb[dst] + obar);

            float llo = (bf_lo(a0) + bf_hi(a0)) + (bf_lo(a2) + bf_hi(a2));
            float lhi = (bf_lo(a1) + bf_hi(a1)) + (bf_lo(a3) + bf_hi(a3));
            llo += __shfl_xor_sync(0xffffffffu, llo, 1); lhi += __shfl_xor_sync(0xffffffffu, lhi, 1);
            llo += __shfl_xor_sync(0xffffffffu, llo, 2); lhi += __shfl_xor_sync(0xffffffffu, lhi, 2);
            st_async_v4(rml0 + opm, __float_as_uint(mlo), __float_as_uint(llo), __float_as_uint(mhi), __float_as_uint(lhi), rml0 + obar);
            if (CL == 8) st_async_v4(rml1 + opm, __float_as_uint(mlo), __float_as_uint(llo), __float_as_uint(mhi), __float_as_uint(lhi), rml1 + obar);
        }
        recv_ctxl(128 + lane);
        asm volatile("bar.arrive 2, 288;" ::: "memory");
    } else if (warp == 10) {
        const int row = uE0 * 8 + lane * 2;
        const bool rowact = lane < nE * 4;
        const int ns = rowact ? P.nslot[row >> 8] : 0;
        const u64* cp = GS(O_CTX + (rowact ? row : 0));
        const int nq = h2 != h1 ? 8 : 4;
        cluster_wait();
        {
            mbar_wait(BAR(GO_Q));
            if (rowact) st_tag2(GS(O_ACTX + row), 0ull, 0ull);
            spin_clks(MLA_DELAY);
            u64 a[8], bb[8], a2[8], b2[8];
            poll_pairs<8, 64>(GS(O_Q + h1 * D_ + lane * 2), nq, a, bb, tag);
            poll_pairs<8, 64>(GS(O_Q + H_ * D_ + h1 * D_ + lane * 2), nq, a2, b2, tag);
#pragma unroll
            for (int i = 0; i < 8; i++) {
                uint32_t hi, lo;
                const int o = S::VBQ + (i >> 2) * 2 * 528 + ((i & 3) * 32 + lane) * 4;
                split2(lo_f(a[i]) + lo_f(a2[i]), lo_f(bb[i]) + lo_f(b2[i]), hi, lo);
                *reinterpret_cast<uint32_t*>(sp + o) = hi; *reinterpret_cast<uint32_t*>(sp + o + 528) = lo;
            }
            __syncwarp();
            if (lane == 0) mbar_arrive(BAR(B_Q));
            TSTAMP(11);
        }
        {
            mbar_wait(BAR(GO_CTX));
            TSTAMP(56);
            u64 w0 = 0ull, w1 = 0ull;
            acc_wait(GS(O_ACTX + (rowact ? row : 0)), ns, w0, w1);
            TSTAMP(57);
            float v0 = acc_val(w0), v1 = acc_val(w1);
            if (__any_sync(0xffffffffu, acc_ovf(w0) || acc_ovf(w1))) {
                u64 a[MAXSLOT], bb[MAXSLOT];
                poll_pairs<MAXSLOT, H_ * D_>(cp, ns, a, bb, tag);
                v0 = 0.f; v1 = 0.f;
#pragma unroll
                for (int i = 0; i < MAXSLOT; i++) { v0 += lo_f(a[i]); v1 += lo_f(bb[i]); }
            }
            uint32_t hi, lo; split2(v0, v1, hi, lo);
            *reinterpret_cast<uint32_t*>(sp + S::VBE + lane * 4) = hi;
            *reinterpret_cast<uint32_t*>(sp + S::VBE + 144 + lane * 4) = lo;
            __syncwarp();
            if (lane == 0) mbar_arrive(BAR(B_E));
            TSTAMP(12);
        }
    } else if (warp == 11) {
        const int half = lane & 1;
        const bool own = rank < 7;
        const int col = (own ? rank * 64 : 0) + (lane >> 3) * 16 + (lane & 7);
        u64* x1d = GS(O_X1 + (rank * 16 + cid) * 64 + lane * 2);
        u64* x2d = GS(O_X2 + (rank * 16 + cid) * 64 + lane * 2);
        u64* ap1 = GS(O_ACC + rank * 64 + lane * 2);
        if (lane == 0) {
            if (own) { mbar_expect_tx(BAR(B_RS1), 2048); if (isF) mbar_expect_tx(BAR(B_RS2), 2048); }
            if (isF) { mbar_expect_tx(BAR(B_FAC), 7 * 256); mbar_expect_tx(BAR(B_F2), 7 * 8); }
        }
        mbar_wait(BAR(B_X));
        const float x0 = __bfloat162float(*reinterpret_cast<const __nv_bfloat16*>(sp + S::XS + col * 2));
        const float x1 = __bfloat162float(*reinterpret_cast<const __nv_bfloat16*>(sp + S::XS + col * 2 + 16));
        float piv = 0.f;
#pragma unroll
        for (int i = 0; i < 7; i++) { const uint32_t w = lds32(sb + S::XS + (i * 32 + lane) * 4); piv += bf_lo(w) + bf_hi(w); }
        piv = wsum(piv) * (1.f / M_);
        constexpr int NB = W / 128;
        const u64* qp = GS(O_QA + rank * (W / 2) + lane * 2);
        cluster_wait();
        {
            mbar_wait(BAR(GO_Q));
            if (own && cid == 0) { st_tag2(ap1, 0ull, 0ull); st_tag2(ap1 + 8 * 64, 0ull, 0ull); }
            mbar_wait(BAR(GO_QA)); spin_clks(MLA_DELAY);
#pragma unroll
            for (int bt = 0; bt < NB; bt++) {
                u64 a[16], bb[16];
                poll_pairs<16, DC_ / 2>(qp + bt * 64, 16, a, bb, tag);
#pragma unroll
                for (int i = 0; i < 16; i++)
                    *reinterpret_cast<uint2*>(sp + S::QA + i * S::QA_PITCH + (bt * 32 + lane) * 8) = make_uint2((uint32_t)a[i], (uint32_t)bb[i]);
            }
            __syncwarp();
            if (lane == 0) { mbar_arrive(BAR(B_QA)); *reinterpret_cast<volatile int*>(sp + S::STAT + 16) = WINC; }
            TSTAMP(15);
        }
        if (own) {
            float hv0 = 0.f, hv1 = 0.f;
            {
                uint32_t rvb[CL];
#pragma unroll
                for (int d = 0; d < CL; d++) rvb[d] = mapa(sb, d);
                const uint32_t vo = S::VBF + (((rank * 4 + (lane >> 3)) * 4 + ((lane & 7) >> 1)) * 2 + half) * 8;
                mbar_wait(BAR(B_RS1));
                TSTAMP(52);
                float2 p[8];
#pragma unroll
                for (int i = 0; i < 8; i++) p[i] = *reinterpret_cast<const float2*>(sp + S::RS + i * 256 + lane * 8);
                const float s0 = ((p[0].x + p[1].x) + (p[2].x + p[3].x)) + ((p[4].x + p[5].x) + (p[6].x + p[7].x));
                const float s1 = ((p[0].y + p[1].y) + (p[2].y + p[3].y)) + ((p[4].y + p[5].y) + (p[6].y + p[7].y));
                const u64 e0 = acc_enc(s0), e1 = acc_enc(s1);
                u64 w0 = atom_add(ap1, e0), w1 = atom_add(ap1 + 1, e1);
                st_tag2(x1d, mkf(s0, tag), mkf(s1, tag));
                TSTAMP(53);
                if (isF) {
                    w0 += e0; w1 += e1;
                    acc_wait(ap1, NC, w0, w1);
                    float v0 = acc_val(w0), v1 = acc_val(w1);
                    if (__any_sync(0xffffffffu, acc_ovf(w0) || acc_ovf(w1))) {
                        u64 a[16], bb[16];
                        poll_pairs<16, 64>(GS(O_X1 + rank * 16 * 64 + lane * 2), NC, a, bb, tag);
                        v0 = 0.f; v1 = 0.f;
#pragma unroll
                        for (int i = 0; i < 16; i++) { v0 += lo_f(a[i]); v1 += lo_f(bb[i]); }
                    }
                    hv0 = x0 + v0; hv1 = x1 + v1;
                    const float o0 = __shfl_xor_sync(0xffffffffu, hv0, 1), o1 = __shfl_xor_sync(0xffffffffu, hv1, 1);
                    uint32_t hiA, loA, hiB, loB;
                    split2((half ? o0 : hv0) - piv, (half ? hv0 : o0) - piv, hiA, loA);
                    split2((half ? o1 : hv1) - piv, (half ? hv1 : o1) - piv, hiB, loB);
#pragma unroll
                    for (int d = 0; d < CL; d++) st_async_v2(rvb[d] + vo, half ? loA : hiA, half ? loB : hiB, rvb[d] + S::BARS + 8 * B_FAC);
                    TSTAMP(13);
                    const float d0 = hv0 - piv, d1 = hv1 - piv;
                    float s1 = d0 + d1, s2 = d0 * d0 + d1 * d1;
#pragma unroll
                    for (int o = 16; o > 0; o >>= 1) { s1 += __shfl_xor_sync(0xffffffffu, s1, o); s2 += __shfl_xor_sync(0xffffffffu, s2, o); }
                    if (lane < CL) { const uint32_t rb = mapa(sb, lane); st_async_v2(rb + S::STAT + 64 + rank * 8, __float_as_uint(s1), __float_as_uint(s2), rb + S::BARS + 8 * B_F2); }
                }
            }
            if (isF) {
                mbar_wait(BAR(B_RS2));
                TSTAMP(54);
                float2 p[8];
#pragma unroll
                for (int i = 0; i < 8; i++) p[i] = *reinterpret_cast<const float2*>(sp + S::RS + 2048 + i * 256 + lane * 8);
                const float s0 = ((p[0].x + p[1].x) + (p[2].x + p[3].x)) + ((p[4].x + p[5].x) + (p[6].x + p[7].x));
                const float s1 = ((p[0].y + p[1].y) + (p[2].y + p[3].y)) + ((p[4].y + p[5].y) + (p[6].y + p[7].y));
                constexpr int NFC = NFCTA / CL;
                u64 enc[2], old[2];
                enc[0] = acc_enc(s0); enc[1] = acc_enc(s1);
                old[0] = atom_add(ap1 + 8 * 64, enc[0]); old[1] = atom_add(ap1 + 8 * 64 + 1, enc[1]);
                st_tag2(x2d, mkf(s0, tag), mkf(s1, tag));
                if (b == 0 && lane == 0) asm volatile("st.relaxed.gpu.global.u32 [%0], %1;" ::"l"(g_s + O_EPOCH), "r"(tag == 65535u ? 0u : tag) : "memory");
#pragma unroll
                for (int k = 0; k < 2; k++) {
                    const u64 tot = old[k] + enc[k];
                    if (acc_cnt(tot) == NFC) {
                        float v = acc_val(tot);
                        if (acc_ovf(tot)) {
                            v = 0.f;
                            for (int c = 0; c < NFC; c++) {
                                u64 a, bb; int lim = 0;
                                do { ld_tag2(GS(O_X2 + (rank * 16 + c) * 64 + lane * 2), a, bb); } while (!tag_ok(a, bb, tag) && ++lim < SPIN_LIMIT);
                                v += lo_f(k ? bb : a);
                            }
                        }
                        P.out[col + 8 * k] = __float2bfloat16((k ? hv1 : hv0) + v);
                    }
                }
                TSTAMP(14);
            }
        }
    } else {
        const int mi = lane >> 3, r = lane & 7;
        if (warp < nE) {
            const int u = uE0 + warp;
            u64* dq = GS(O_Q + (u & 1) * (H_ * D_) + (u >> 1) * 16 + g);
            mbar_wait(BAR(B_X));
            uint32_t xw[7], bx[14][2];
#pragma unroll
            for (int i = 0; i < 7; i++) xw[i] = lds32(sb + S::XS + (i * 32 + lane) * 4);
#pragma unroll
            for (int ks = 0; ks < 14; ks++) {
                const uint32_t xa = sb + S::XS + ((u & 1) * 224 + ks * 16 + 2 * t) * 2;
                bx[ks][0] = lds32(xa); bx[ks][1] = lds32(xa + 16);
                if (g != 0) { bx[ks][0] = bx[ks][1] = g == 1 ? 0x3f803f80u : 0u; }
            }
            float s = 0.f;
#pragma unroll
            for (int i = 0; i < 7; i++) s += bf_lo(xw[i]) + bf_hi(xw[i]);
            const float mean = wsum(s) * (1.f / M_);
            float vs = 0.f;
#pragma unroll
            for (int i = 0; i < 7; i++) { const float d0 = bf_lo(xw[i]) - mean, d1 = bf_hi(xw[i]) - mean; vs += d0 * d0 + d1 * d1; }
            const float rstd = rsqrtf(wsum(vs) * (1.f / M_) + 1e-5f);
            float c[2][4];
#pragma unroll
            for (int i = 0; i < 2; i++) { c[i][0] = c[i][1] = c[i][2] = c[i][3] = 0.f; }
            const int rr = (mi >> 1) * 8 + r;
            const uint32_t wa = sb + S::RING + warp * 8192 + rr * 32 + ((((mi & 1) ^ (rr >> 2)) & 1) << 4);
            WAITG(warp);
#pragma unroll
            for (int ks = 0; ks < 14; ks++) {
                uint32_t a[4];
                ldsm4t(a, wa + ks * 512);
                mma16816(c[ks & 1], a, bx[ks][0], bx[ks][1]);
            }
            if (t == 0) {
                st_tag1(dq, mkf(((c[0][0] + c[1][0]) - mean * (c[0][1] + c[1][1])) * rstd, tag));
                st_tag1(dq + 8, mkf(((c[0][2] + c[1][2]) - mean * (c[0][3] + c[1][3])) * rstd, tag));
            }
            if (tid == 0) mbar_arrive(BAR(GO_Q));
            TSTAMP(1);
        }
        __syncwarp();
        cluster_wait();
        {
            mbar_wait(BAR(B_Q));
            uint32_t bq[16][2];
#pragma unroll
            for (int ks = 0; ks < 16; ks++) {
                bq[ks][0] = g < 4 ? lds32(sb + S::VBQ + g * 528 + (ks * 16 + 2 * t) * 2) : 0u;
                bq[ks][1] = g < 4 ? lds32(sb + S::VBQ + g * 528 + (ks * 16 + 2 * t + 8) * 2) : 0u;
            }
            TSTAMP(2);
            for (int un = warp; un < nB; un += 8) {
                WAITG(G_UK + un);
                const uint32_t rowa = sb + S::RING + (G_UK + un) * 8192 + ((mi & 1) * 8 + r) * 128;
                float c[4][4];
#pragma unroll
                for (int i = 0; i < 4; i++) { c[i][0] = c[i][1] = c[i][2] = c[i][3] = 0.f; }
#pragma unroll
                for (int ks = 0; ks < 16; ks++) {
                    uint32_t a[4];
                    const int ch = (ks & 3) * 2 + (mi >> 1);
                    ldsm4(a, rowa + (ks >> 2) * 2048 + ((ch ^ r) << 4));
                    mma16816(c[ks & 3], a, bq[ks][0], bq[ks][1]);
                }
                constexpr float SC = 0.0625f * 1.4426950408889634f;
                const float va = (((c[0][0] + c[1][0]) + (c[2][0] + c[3][0])) + ((c[0][1] + c[1][1]) + (c[2][1] + c[3][1]))) * SC;
                const float vb = (((c[0][2] + c[1][2]) + (c[2][2] + c[3][2])) + ((c[0][3] + c[1][3]) + (c[2][3] + c[3][3]))) * SC;
                const uint32_t wa = pack_bf16(va, __shfl_down_sync(0xffffffffu, va, 4));
                const uint32_t wb = pack_bf16(vb, __shfl_down_sync(0xffffffffu, vb, 4));
                const uint32_t wa2 = __shfl_down_sync(0xffffffffu, wa, 8), wb2 = __shfl_down_sync(0xffffffffu, wb, 8);
                const int u = uB0 + un;
                if (t == ((u >> 6) == h1 ? 0 : 1) && (g & 3) == 0) {
                    u64* dst = GS(O_QA + u * 8 + (g >> 1));
                    st_tag2(dst, mk(wa, tag), mk(wa2, tag));
                    st_tag2(dst + 4, mk(wb, tag), mk(wb2, tag));
                }
            }
            __syncwarp();
            if (lane == 0) mbar_arrive(BAR(B_REL + 0));
            if (tid == 0) { mbar_arrive(BAR(GO_QA)); *reinterpret_cast<volatile int*>(sp + S::STAT + 16) = WINB; }
            TSTAMP(3);

        }
        if (warp < 4) {
            const uint32_t pd0 = mapa(sb + S::PART + rank * 1024 + lane * 16, 2 * warp), pd1 = mapa(sb + S::PART + rank * 1024 + lane * 16, 2 * warp + 1);
            const uint32_t pb0 = mapa(BAR(B_PART), 2 * warp), pb1 = mapa(BAR(B_PART), 2 * warp + 1);
            const uint32_t sc_off = ((mi >> 1) * 8 + r) * 128;
            mbar_wait(BAR(B_QA));
            uint32_t qa[8][4];
#pragma unroll
            for (int ks = 0; ks < 8; ks++) {
                const uint32_t a = sb + S::QA + g * S::QA_PITCH + (ks * 16 + 2 * t) * 2;
                qa[ks][0] = lds32(a); qa[ks][1] = lds32(a + 8 * S::QA_PITCH); qa[ks][2] = lds32(a + 16); qa[ks][3] = lds32(a + 8 * S::QA_PITCH + 16);
            }
            TSTAMP(4);
#pragma unroll 1
            for (int j = 0; j < NCH; j++) {
                if (j * 4 + warp < nKG) {
                    const int gr = G_C + j * 4 + warp;
                    const uint32_t rowa = SLOT(gr) + sc_off;
                    WAITG(gr);
                    float s[4][4];
#pragma unroll
                    for (int i = 0; i < 4; i++) { s[i][0] = s[i][1] = s[i][2] = s[i][3] = 0.f; }
#pragma unroll
                    for (int ks = 0; ks < 8; ks++) {
                        uint32_t b0[4], b1[4];
                        const uint32_t ad = rowa + (ks >> 2) * 4096 + ((((ks & 3) * 2 + (mi & 1)) ^ r) << 4);
                        ldsm4(b0, ad); ldsm4(b1, ad + 2048);
                        mma16816(s[0], qa[ks], b0[0], b0[1]); mma16816(s[1], qa[ks], b0[2], b0[3]);
                        mma16816(s[2], qa[ks], b1[0], b1[1]); mma16816(s[3], qa[ks], b1[2], b1[3]);
                    }
                    if (j >= 2) mbar_wait(BAR(B_P + j - 2));
                    const uint32_t o = (j & 1) * 8192;
                    st_async_v4(pd0 + o, __float_as_uint(s[0][0]), __float_as_uint(s[0][1]), __float_as_uint(s[0][2]), __float_as_uint(s[0][3]), pb0 + 8 * j);
                    st_async_v4(pd0 + o + 512, __float_as_uint(s[1][0]), __float_as_uint(s[1][1]), __float_as_uint(s[1][2]), __float_as_uint(s[1][3]), pb0 + 8 * j);
                    st_async_v4(pd1 + o, __float_as_uint(s[2][0]), __float_as_uint(s[2][1]), __float_as_uint(s[2][2]), __float_as_uint(s[2][3]), pb1 + 8 * j);
                    st_async_v4(pd1 + o + 512, __float_as_uint(s[3][0]), __float_as_uint(s[3][1]), __float_as_uint(s[3][2]), __float_as_uint(s[3][3]), pb1 + 8 * j);
                    TSTAMP(24 + j);
                }
                if (lane == 0) mbar_arrive(BAR(B_REL + 1 + j));
            }
        } else {
            const int pw = warp - 4;
            const uint32_t pv_off = (pw >> 1) * 4096 + ((mi & 1) * 8 + r) * 128;
            const uint32_t c0 = ((((pw & 1) * 4 + (mi >> 1)) ^ r) << 4), c1 = ((((pw & 1) * 4 + 2 + (mi >> 1)) ^ r) << 4);
            u64* gp = GS(O_PART + (cid * H_ + g) * (DC_ / 2) + (rank * W + pw * 32) / 2 + 2 * t);
            mbar_wait(BAR(B_QA));
            st_tag2(gp, 0ull, 0ull); st_tag2(gp + 8, 0ull, 0ull); st_tag2(gp + 8 * (DC_ / 2), 0ull, 0ull); st_tag2(gp + 8 * (DC_ / 2) + 8, 0ull, 0ull);
            float acc[4][4], acc2[4][4];
#pragma unroll
            for (int i = 0; i < 4; i++) { acc[i][0] = acc[i][1] = acc[i][2] = acc[i][3] = 0.f; acc2[i][0] = acc2[i][1] = acc2[i][2] = acc2[i][3] = 0.f; }
            float Mlo = -INFINITY, Mhi = -INFINITY, Llo = 0.f, Lhi = 0.f;
#pragma unroll 1
            for (int j = 0; j < NCH; j++) {
                const int nt = min(CL, T - j * CL);
                const int g0 = G_C + j * 4;
                const uint32_t pml = sb + S::PML + j * CL * 128 + g * 16, ppb = sb + S::PBUF + j * CL * 512 + lane * 16;
                uint32_t va[4];
#pragma unroll
                for (int gi = 0; gi < 4; gi++) va[gi] = SLOT(g0 + (gi * 2 < nt ? gi : 0)) + pv_off;
                mbar_wait(BAR(B_P + j));
                if (warp == 4 && lane == 0) { TSTAMP2(32 + j); }
                float flo[CL], fhi[CL];
                bool stdref = true;
                {
                    uint4 ml[CL];
#pragma unroll
                    for (int tl = 0; tl < CL; tl++) ml[tl] = lds128(pml + (tl < nt ? tl : 0) * 128);
#pragma unroll
                    for (int tl = 0; tl < CL; tl++) stdref = stdref && __uint_as_float(ml[tl].x) == Mlo && __uint_as_float(ml[tl].z) == Mhi;
                    stdref = __all_sync(0xffffffffu, stdref);
                    if (stdref) {
#pragma unroll
                        for (int tl = 0; tl < CL; tl++) { Llo += tl < nt ? __uint_as_float(ml[tl].y) : 0.f; Lhi += tl < nt ? __uint_as_float(ml[tl].w) : 0.f; flo[tl] = fhi[tl] = 0.f; }
                    } else {
                        float nlo = Mlo, nhi = Mhi;
#pragma unroll
                        for (int tl = 0; tl < CL; tl++) {
                            if (tl >= nt) { ml[tl].x = 0xff800000u; ml[tl].z = 0xff800000u; }
                            nlo = fmaxf(nlo, __uint_as_float(ml[tl].x)); nhi = fmaxf(nhi, __uint_as_float(ml[tl].z));
                        }
                        nlo = nlo > Mlo + REF_SLACK ? nlo : Mlo; nhi = nhi > Mhi + REF_SLACK ? nhi : Mhi;
                        const float rlo = ex2(Mlo - nlo), rhi = ex2(Mhi - nhi);
                        Mlo = nlo; Mhi = nhi; Llo *= rlo; Lhi *= rhi;
#pragma unroll
                        for (int i = 0; i < 4; i++) {
                            acc[i][0] = (acc[i][0] + acc2[i][0]) * rlo; acc[i][1] = (acc[i][1] + acc2[i][1]) * rlo;
                            acc[i][2] = (acc[i][2] + acc2[i][2]) * rhi; acc[i][3] = (acc[i][3] + acc2[i][3]) * rhi;
                            acc2[i][0] = acc2[i][1] = acc2[i][2] = acc2[i][3] = 0.f;
                        }
#pragma unroll
                        for (int tl = 0; tl < CL; tl++) {
                            flo[tl] = ex2(__uint_as_float(ml[tl].x) - Mlo); fhi[tl] = ex2(__uint_as_float(ml[tl].z) - Mhi);
                            Llo += flo[tl] * __uint_as_float(ml[tl].y); Lhi += fhi[tl] * __uint_as_float(ml[tl].w);
                        }
                    }
                }
                if (stdref) {
#pragma unroll
                    for (int tl = 0; tl < CL; tl++) {
                        if (tl >= 2 && (tl & ~1) >= nt) break;
                        const uint4 pv = lds128(ppb + tl * 512);
                        uint32_t v0[4], v1[4];
                        ldsm4t(v0, va[tl >> 1] + (tl & 1) * 2048 + c0); ldsm4t(v1, va[tl >> 1] + (tl & 1) * 2048 + c1);
                        const uint32_t pa[4] = {pv.x, pv.y, pv.z, pv.w};
                        if (tl & 1) { mma16816(acc2[0], pa, v0[0], v0[1]); mma16816(acc2[1], pa, v0[2], v0[3]); mma16816(acc2[2], pa, v1[0], v1[1]); mma16816(acc2[3], pa, v1[2], v1[3]); }
                        else { mma16816(acc[0], pa, v0[0], v0[1]); mma16816(acc[1], pa, v0[2], v0[3]); mma16816(acc[2], pa, v1[0], v1[1]); mma16816(acc[3], pa, v1[2], v1[3]); }
                    }
                } else {
#pragma unroll
                    for (int tl = 0; tl < CL; tl++) {
                        const uint4 pv = lds128(ppb + (tl < nt ? tl : 0) * 512);
                        uint32_t v0[4], v1[4];
                        ldsm4t(v0, va[tl >> 1] + (tl & 1) * 2048 + c0); ldsm4t(v1, va[tl >> 1] + (tl & 1) * 2048 + c1);
                        const uint32_t pa[4] = {pv.x, pv.y, pv.z, pv.w};
                        float tt[4][4];
#pragma unroll
                        for (int i = 0; i < 4; i++) { tt[i][0] = tt[i][1] = tt[i][2] = tt[i][3] = 0.f; }
                        mma16816(tt[0], pa, v0[0], v0[1]); mma16816(tt[1], pa, v0[2], v0[3]); mma16816(tt[2], pa, v1[0], v1[1]); mma16816(tt[3], pa, v1[2], v1[3]);
#pragma unroll
                        for (int i = 0; i < 4; i++) {
                            acc[i][0] += flo[tl] * tt[i][0]; acc[i][1] += flo[tl] * tt[i][1]; acc[i][2] += fhi[tl] * tt[i][2]; acc[i][3] += fhi[tl] * tt[i][3];
                        }
                    }
                }
                if (lane == 0) mbar_arrive(BAR(B_REL + 1 + j));
                if (warp == 4 && lane == 0) { TSTAMP2(38 + j); }
            }
            const float ilo = __fdividef(1.f, Llo), ihi = __fdividef(1.f, Lhi);
            const uint32_t wlo = __float_as_uint(Mlo + __log2f(Llo)), whi = __float_as_uint(Mhi + __log2f(Lhi));
#pragma unroll
            for (int q = 0; q < 2; q++) {
                st_tag2(gp + q * 8, mk(pack_bf16((acc[2 * q][0] + acc2[2 * q][0]) * ilo, (acc[2 * q][1] + acc2[2 * q][1]) * ilo), tag | (wlo & 0xffff0000u)),
                                    mk(pack_bf16((acc[2 * q + 1][0] + acc2[2 * q + 1][0]) * ilo, (acc[2 * q + 1][1] + acc2[2 * q + 1][1]) * ilo), tag | (wlo << 16)));
                st_tag2(gp + q * 8 + 8 * (DC_ / 2), mk(pack_bf16((acc[2 * q][2] + acc2[2 * q][2]) * ihi, (acc[2 * q][3] + acc2[2 * q][3]) * ihi), tag | (whi & 0xffff0000u)),
                                                    mk(pack_bf16((acc[2 * q + 1][2] + acc2[2 * q + 1][2]) * ihi, (acc[2 * q + 1][3] + acc2[2 * q + 1][3]) * ihi), tag | (whi << 16)));
            }
            if (warp == 4 && lane == 0) { TSTAMP2(5); mbar_arrive(BAR(GO_D)); }
        }
        {
            uint32_t wa[MAXUB][2][4];
            const uint32_t aoff = (warp >> 1) * 2048 + ((mi >> 1) * 8 + r) * 128;
            const int ch0 = (warp & 1) * 4 + (mi & 1);
            auto load_unit = [&](int ks) {
                if (ks < nB) {
                    WAITG(G_UV + ks);
                    const uint32_t ua = SLOT(G_UV + ks) + aoff;
                    ldsm4t(wa[ks][0], ua + ((ch0 ^ r) << 4));
                    ldsm4t(wa[ks][1], ua + (((ch0 + 2) ^ r) << 4));
                } else {
#pragma unroll
                    for (int k = 0; k < 4; k++) { wa[ks][0][k] = 0u; wa[ks][1][k] = 0u; }
                }
            };
#pragma unroll
            for (int ks = 0; ks < MLA_KPRE; ks++) load_unit(ks);
            TSTAMP(50);
            if (warp < 4) recv_ctxl(tid);
            TSTAMP(6);
            const unsigned char* vb = sp + S::VBD + (t * 4 + (g & 3)) * 8;
            const int hh = t ? h2 : h1;
            u64* gc = GS(O_CTX + ((b - P.firstB[hh]) * H_ + hh) * D_ + warp * 32 + g);
            u64* ga = GS(O_ACTX + hh * D_ + warp * 32 + g);
            asm volatile("bar.sync 2, 288;" ::: "memory");
            TSTAMP(51);
            float c[4][4];
#pragma unroll
            for (int i = 0; i < 4; i++) { c[i][0] = c[i][1] = c[i][2] = c[i][3] = 0.f; }
#pragma unroll
            for (int ks = 0; ks < MAXUB; ks++) {
                if (ks >= MLA_KPRE) load_unit(ks);
                const uint2 bw = *reinterpret_cast<const uint2*>(vb + ks * 128);
                const uint32_t b0 = g < 4 ? bw.x : 0u, b1 = g < 4 ? bw.y : 0u;
                mma16816(c[(ks & 1) * 2], wa[ks][0], b0, b1);
                mma16816(c[(ks & 1) * 2 + 1], wa[ks][1], b0, b1);
            }
            if (lane == 0) mbar_arrive(BAR(B_REL + 6));
            if (t == 0 || (t == 1 && h2 != h1)) {
                const float o0 = (c[0][0] + c[2][0]) + (c[0][1] + c[2][1]), o1 = (c[0][2] + c[2][2]) + (c[0][3] + c[2][3]);
                const float o2 = (c[1][0] + c[3][0]) + (c[1][1] + c[3][1]), o3 = (c[1][2] + c[3][2]) + (c[1][3] + c[3][3]);
                red_add(ga, acc_enc(o0)); red_add(ga + 8, acc_enc(o1)); red_add(ga + 16, acc_enc(o2)); red_add(ga + 24, acc_enc(o3));
                st_tag1(gc, mkf(o0, tag)); st_tag1(gc + 8, mkf(o1, tag)); st_tag1(gc + 16, mkf(o2, tag)); st_tag1(gc + 24, mkf(o3, tag));
            }
            if (tid == 0) mbar_arrive(BAR(GO_CTX));
            TSTAMP(7);
        }
        {
            uint32_t wa[4][3][4];
            uint32_t rsd[4];
#pragma unroll
            for (int i = 0; i < 4; i++) rsd[i] = mapa(sb, min((warp >> 2) + 2 * i, 6));
            const uint32_t rso = S::RS + rank * 256 + ((warp & 3) * 8 + g) * 8;
            const uint32_t vb = sb + S::VBE + (g & 1) * 144 + 4 * t;
#pragma unroll
            for (int ks = 0; ks < 3; ks++) {
                if (ks * 2 < nE) WAITG(G_WO + ks * 2);
                if (ks * 2 + 1 < nE) WAITG(G_WO + ks * 2 + 1);
                const uint32_t ua = SLOT(G_WO + min(ks * 2 + (mi >> 1), nE - 1)) + r * 128;
#pragma unroll
                for (int i = 0; i < 4; i++) {
                    const int mt = min(warp + 8 * i, 27);
                    const int ch = (mt & 3) * 2 + (mi & 1);
                    ldsm4t(wa[i][ks], ua + (mt >> 2) * 1024 + ((ch ^ r) << 4));
                }
            }
            mbar_wait(BAR(B_E));
            uint32_t bv[3][2];
#pragma unroll
            for (int ks = 0; ks < 3; ks++) {
                bv[ks][0] = lds32(vb + ks * 32); bv[ks][1] = lds32(vb + ks * 32 + 16);
                if (g >= 2) { bv[ks][0] = 0u; bv[ks][1] = 0u; }
            }
            float c[4][4];
#pragma unroll
            for (int i = 0; i < 4; i++) { c[i][0] = c[i][1] = c[i][2] = c[i][3] = 0.f; }
#pragma unroll
            for (int ks = 0; ks < 3; ks++)
#pragma unroll
                for (int i = 0; i < 4; i++) mma16816(c[i], wa[i][ks], bv[ks][0], bv[ks][1]);
#pragma unroll
            for (int i = 0; i < 4; i++)
                if (t == 0 && warp + 8 * i < 28) st_async_v2(rsd[i] + rso, __float_as_uint(c[i][0] + c[i][1]), __float_as_uint(c[i][2] + c[i][3]), rsd[i] + S::BARS + 8 * B_RS1);
            TSTAMP(8);
        }
        if (isF) {
            uint32_t wg[4][4], wu[4][4], wd[4][4];
            uint32_t rsd[4];
#pragma unroll
            for (int i = 0; i < 4; i++) rsd[i] = mapa(sb, min((warp >> 2) + 2 * i, 6));
            const uint32_t rso = S::RS + 2048 + rank * 256 + ((warp & 3) * 8 + g) * 8;
            const int nh = g < 2 ? (warp < 4 ? 4 : 3) : 0;
#pragma unroll
            for (int i = 0; i < 4; i++) WAITG(G_FG + i);
#pragma unroll
            for (int i = 0; i < 4; i++) {
                const int ks = min(warp + 8 * i, 27);
                const int row = ks * 16 + (mi >> 1) * 8 + r;
                const int hb = row >= 224, rr = row - hb * 224;
                const uint32_t o = rr * 32 + ((((mi & 1) ^ (rr >> 2)) & 1) << 4);
                ldsm4t(wg[i], SLOT(G_FG + hb) + o);
                ldsm4t(wu[i], SLOT(G_FG + 2 + hb) + o);
            }
            WAITG(G_WD); WAITG(G_WD + 1);
#pragma unroll
            for (int i = 0; i < 4; i++) {
                const int mt = min(warp + 8 * i, 27);
                const int ch = (mt & 3) * 2 + (mi & 1);
                ldsm4t(wd[i], SLOT(G_WD + (mi >> 1)) + (mt >> 2) * 1024 + r * 128 + ((ch ^ r) << 4));
            }
            uint2 hf[4];
            mbar_wait(BAR(B_FAC));
#pragma unroll
            for (int i = 0; i < 4; i++) {
                hf[i] = *reinterpret_cast<const uint2*>(sp + S::VBF + (((warp + 8 * (i < nh ? i : 0)) * 4 + t) * 2 + (g & 1)) * 8);
                if (i >= nh) hf[i] = make_uint2(0u, 0u);
            }
            TSTAMP(19);
            float cg[2][4], cu[2][4];
#pragma unroll
            for (int i = 0; i < 2; i++) { cg[i][0] = cg[i][1] = cg[i][2] = cg[i][3] = 0.f; cu[i][0] = cu[i][1] = cu[i][2] = cu[i][3] = 0.f; }
#pragma unroll
            for (int i = 0; i < 4; i++) {
                uint32_t b0 = hf[i].x, b1 = hf[i].y;
                if (g == 2 && warp + 8 * i < 28) { b0 = b1 = 0x3f803f80u; }
                mma16816(cg[i & 1], wg[i], b0, b1);
                mma16816(cu[i & 1], wu[i], b0, b1);
            }
            float* red = reinterpret_cast<float*>(sp + S::RED);
            if (t < 2) {
                float* rp = red + warp * 64 + t * 32 + g;
                rp[0] = (cg[0][0] + cg[1][0]) + (cg[0][1] + cg[1][1]); rp[8] = (cg[0][2] + cg[1][2]) + (cg[0][3] + cg[1][3]);
                rp[16] = (cu[0][0] + cu[1][0]) + (cu[0][1] + cu[1][1]); rp[24] = (cu[0][2] + cu[1][2]) + (cu[0][3] + cu[1][3]);
            }
            bar_compute();
            float rv[8], rc[8];
#pragma unroll
            for (int w = 0; w < 8; w++) { rv[w] = red[w * 64 + lane]; rc[w] = red[w * 64 + 32 + lane]; }
            TSTAMP(60);
            mbar_wait(BAR(B_F2));
            TSTAMP(61);
            float2 st;
            {
                float s1 = 0.f, s2 = 0.f;
#pragma unroll
                for (int i = 0; i < 7; i++) { const float2 p = *reinterpret_cast<const float2*>(sp + S::STAT + 64 + i * 8); s1 += p.x; s2 += p.y; }
                st.x = s1 * (1.f / M_);
                st.y = rsqrtf(fmaxf(s2 * (1.f / M_) - st.x * st.x, 0.f) + 1e-5f);
            }
            const float sv = ((rv[0] + rv[1]) + (rv[2] + rv[3])) + ((rv[4] + rv[5]) + (rv[6] + rv[7]));
            const float sc = ((rc[0] + rc[1]) + (rc[2] + rc[3])) + ((rc[4] + rc[5]) + (rc[6] + rc[7]));
            const float v = (sv - st.x * sc) * st.y;
            const float uu = __shfl_down_sync(0xffffffffu, v, 16);
            const float av = __fdividef(uu, 1.f + ex2(-1.4426950408889634f * v));
            const float a0 = __shfl_sync(0xffffffffu, av, 2 * t), a1 = __shfl_sync(0xffffffffu, av, 2 * t + 1);
            const float a2 = __shfl_sync(0xffffffffu, av, 2 * t + 8), a3 = __shfl_sync(0xffffffffu, av, 2 * t + 9);
            uint32_t h0, l0, h1b, l1b;
            split2(a0, a1, h0, l0); split2(a2, a3, h1b, l1b);
            const uint32_t b0 = g == 0 ? h0 : (g == 1 ? l0 : 0u), b1 = g == 0 ? h1b : (g == 1 ? l1b : 0u);
#pragma unroll
            for (int i = 0; i < 4; i++) {
                float c[4] = {0.f, 0.f, 0.f, 0.f};
                mma16816(c, wd[i], b0, b1);
                if (t == 0 && warp + 8 * i < 28) st_async_v2(rsd[i] + rso, __float_as_uint(c[0] + c[1]), __float_as_uint(c[2] + c[3]), rsd[i] + S::BARS + 8 * B_RS2);
            }
            TSTAMP(9);
        }
    }
}

constexpr int FB_Q = 0, FB_QA = FB_Q + H_ * D_, FB_S = FB_QA + H_ * DC_, FB_CL = FB_S + H_ * SK_, FB_CTX = FB_CL + H_ * DC_,
              FB_H = FB_CTX + H_ * D_, FB_A = FB_H + 512, FB_END = FB_A + F_;
static_assert(FB_END <= 2 * O_EPOCH, "fallback scratch");
__device__ __forceinline__ float* fbs() { return reinterpret_cast<float*>(g_s); }
__device__ __forceinline__ float bsum(float v, float* red) {
    v = wsum(v);
    __syncthreads();
    if ((threadIdx.x & 31) == 0) red[threadIdx.x >> 5] = v;
    __syncthreads();
    float s = 0.f;
    for (int i = 0; i < (int)(blockDim.x >> 5); i++) s += red[i];
    return s;
}
template <bool GLU>
__global__ void fb_ln_gemv(const __nv_bfloat16* xb, const float* xf, const __nv_bfloat16* w0, const __nv_bfloat16* w1, int N, float* y) {
    __shared__ float xs[M_], red[8];
    float s = 0.f;
    for (int i = threadIdx.x; i < M_; i += blockDim.x) { xs[i] = xb ? __bfloat162float(xb[i]) : xf[i]; s += xs[i]; }
    const float mean = bsum(s, red) * (1.f / M_);
    float vs = 0.f;
    for (int i = threadIdx.x; i < M_; i += blockDim.x) { const float d = xs[i] - mean; vs += d * d; }
    const float rstd = rsqrtf(bsum(vs, red) * (1.f / M_) + 1e-5f);
    const int n = blockIdx.x * blockDim.x + threadIdx.x;
    float a = 0.f, u = 0.f;
    for (int m = 0; m < M_; m++) {
        const float xn = (xs[m] - mean) * rstd;
        a += xn * __bfloat162float(w0[(size_t)m * N + n]);
        if (GLU) u += xn * __bfloat162float(w1[(size_t)m * N + n]);
    }
    y[n] = GLU ? u / (1.f + __expf(-a)) : a;
}
__global__ void fb_qabs(const __nv_bfloat16* wuk) {
    const int row = blockIdx.x * 8 + (threadIdx.x >> 5), lane = threadIdx.x & 31, h = row & 15, c = row >> 4;
    float s = 0.f;
    for (int d = lane; d < D_; d += 32) s += fbs()[FB_Q + h * D_ + d] * __bfloat162float(wuk[(size_t)row * D_ + d]);
    s = wsum(s);
    if (lane == 0) fbs()[FB_QA + h * DC_ + c] = s * 0.0625f;
}
__global__ void fb_scores(const __nv_bfloat16* ckv) {
    const int k = blockIdx.x * 8 + (threadIdx.x >> 5), lane = threadIdx.x & 31;
    float s[H_];
#pragma unroll
    for (int h = 0; h < H_; h++) s[h] = 0.f;
    for (int c = lane; c < DC_; c += 32) {
        const float v = __bfloat162float(ckv[(size_t)k * DC_ + c]);
#pragma unroll
        for (int h = 0; h < H_; h++) s[h] += v * fbs()[FB_QA + h * DC_ + c];
    }
#pragma unroll
    for (int h = 0; h < H_; h++) { const float t = wsum(s[h]); if (lane == 0) fbs()[FB_S + h * SK_ + k] = t; }
}
__global__ void fb_softmax() {
    __shared__ float red[8];
    float* s = fbs() + FB_S + blockIdx.x * SK_;
    float m = -INFINITY;
    for (int k = threadIdx.x; k < SK_; k += 256) m = fmaxf(m, s[k]);
#pragma unroll
    for (int o = 16; o > 0; o >>= 1) m = fmaxf(m, __shfl_xor_sync(0xffffffffu, m, o));
    if ((threadIdx.x & 31) == 0) red[threadIdx.x >> 5] = m;
    __syncthreads();
    for (int i = 0; i < 8; i++) m = fmaxf(m, red[i]);
    float l = 0.f;
    for (int k = threadIdx.x; k < SK_; k += 256) { const float e = __expf(s[k] - m); s[k] = e; l += e; }
    l = 1.f / bsum(l, red);
    for (int k = threadIdx.x; k < SK_; k += 256) s[k] *= l;
}
__global__ void fb_ctxl(const __nv_bfloat16* ckv) {
    __shared__ float part[8][H_][32];
    const int lane = threadIdx.x & 31, w = threadIdx.x >> 5, c = blockIdx.x * 32 + lane;
    float a[H_];
#pragma unroll
    for (int h = 0; h < H_; h++) a[h] = 0.f;
    for (int k = w; k < SK_; k += 8) {
        const float v = __bfloat162float(ckv[(size_t)k * DC_ + c]);
#pragma unroll
        for (int h = 0; h < H_; h++) a[h] += v * fbs()[FB_S + h * SK_ + k];
    }
#pragma unroll
    for (int h = 0; h < H_; h++) part[w][h][lane] = a[h];
    __syncthreads();
    for (int h = w; h < H_; h += 8) {
        float s = 0.f;
        for (int i = 0; i < 8; i++) s += part[i][h][lane];
        fbs()[FB_CL + h * DC_ + c] = s;
    }
}
__global__ void fb_ctx(const __nv_bfloat16* wuv) {
    const int h = blockIdx.x, d = threadIdx.x;
    float s = 0.f;
    for (int c = 0; c < DC_; c++) s += fbs()[FB_CL + h * DC_ + c] * __bfloat162float(wuv[((size_t)c * H_ + h) * D_ + d]);
    fbs()[FB_CTX + h * D_ + d] = s;
}
__global__ void fb_gemv_res(const float* v, int K, const __nv_bfloat16* w, const __nv_bfloat16* bb, const float* bf, float* yf, __nv_bfloat16* yb) {
    const int n = blockIdx.x * blockDim.x + threadIdx.x;
    float s = bb ? __bfloat162float(bb[n]) : bf[n];
    for (int k = 0; k < K; k++) s += v[k] * __bfloat162float(w[(size_t)k * M_ + n]);
    if (yf) yf[n] = s; else yb[n] = __float2bfloat16(s);
}
void launch_fallback(void* const* d_in, void* d_out) {
    typedef const __nv_bfloat16* cb;
    float* sc = nullptr;
    cudaGetSymbolAddress((void**)&sc, g_s);
    cudaStream_t st = cudaStreamPerThread;
    fb_ln_gemv<false><<<16, 256, 0, st>>>((cb)d_in[0], nullptr, (cb)d_in[2], nullptr, H_ * D_, sc + FB_Q);
    fb_qabs<<<H_ * DC_ / 8, 256, 0, st>>>((cb)d_in[3]);
    fb_scores<<<SK_ / 8, 256, 0, st>>>((cb)d_in[1]);
    fb_softmax<<<H_, 256, 0, st>>>();
    fb_ctxl<<<DC_ / 32, 256, 0, st>>>((cb)d_in[1]);
    fb_ctx<<<H_, D_, 0, st>>>((cb)d_in[4]);
    fb_gemv_res<<<7, 64, 0, st>>>(sc + FB_CTX, H_ * D_, (cb)d_in[5], (cb)d_in[0], nullptr, sc + FB_H, nullptr);
    fb_ln_gemv<true><<<7, 256, 0, st>>>(nullptr, sc + FB_H, (cb)d_in[7], (cb)d_in[8], F_, sc + FB_A);
    fb_gemv_res<<<7, 64, 0, st>>>(sc + FB_A, F_, (cb)d_in[9], nullptr, sc + FB_H, nullptr, (__nv_bfloat16*)d_out);
}

typedef CUresult (*EncodeFn)(CUtensorMap*, CUtensorMapDataType, cuuint32_t, void*, const cuuint64_t*, const cuuint64_t*, const cuuint32_t*,
                             const cuuint32_t*, CUtensorMapInterleave, CUtensorMapSwizzle, CUtensorMapL2promotion, CUtensorMapFloatOOBfill);

struct HostState {
    bool ready;
    int CL;
    const void* ptrs[10];
    Maps tm;
    Params P;
    int smem;
};
HostState g_hs;

bool encode(EncodeFn fn, CUtensorMap* tm, const void* base, const cuuint64_t* dims, const cuuint64_t* strides, const cuuint32_t* box, CUtensorMapSwizzle sw) {
    cuuint32_t es[4] = {1, 1, 1, 1};
    return fn(tm, CU_TENSOR_MAP_DATA_TYPE_BFLOAT16, 4, const_cast<void*>(base), dims, strides, box, es, CU_TENSOR_MAP_INTERLEAVE_NONE, sw,
              CU_TENSOR_MAP_L2_PROMOTION_L2_128B, CU_TENSOR_MAP_FLOAT_OOB_FILL_NONE) == CUDA_SUCCESS;
}

bool plan(HostState& hs, int CL, int NC) {
    Params& P = hs.P;
    const int G = CL * NC;
    if (G < NFCTA || G > MAXG || NC > MAXNC) return false;
    P.G = G; P.NC = NC;
    P.qB = 1024 / G; P.rB = 1024 % G;
    P.qE = 512 / G; P.rE = 512 % G;
    P.lB = G - P.rB; P.lE = P.lB - P.rE > 0 ? P.lB - P.rE : 0;
    const int NKG = SK_ / (CL * 4);
    P.qK = NKG / NC; P.rK = NKG % NC;
    const int mB = P.qB + (P.rB > 0), mE = P.qE + (P.rE > 0), mK = P.qK + (P.rK > 0);
    if (mB > MAXUB || mE > 5 || (mK + 3) / 4 > MAXCH || 2 * mB + mK + 2 * mE + 6 > MAXGR || mE + mB > NSLOT || P.qE < 4) return false;
    for (int h = 0; h < H_; h++) {
        int first = -1, last = -1;
        for (int b = 0; b < G; b++) {
            const int u0 = b * P.qB + (b > P.lB ? b - P.lB : 0), u1 = u0 + P.qB + (b >= P.lB);
            if (u0 < 64 * (h + 1) && u1 > 64 * h) { if (first < 0) first = b; last = b; }
        }
        P.firstB[h] = (unsigned char)first; P.nslot[h] = (unsigned char)(last - first + 1);
        if (last - first + 1 > MAXSLOT) return false;
    }
    return true;
}

template <int CL> int max_clusters() {
    const int smem = SM<CL>::END + 1024;
    if (cudaFuncSetAttribute(mla_kernel<CL>, cudaFuncAttributeMaxDynamicSharedMemorySize, smem) != cudaSuccess) { cudaGetLastError(); return 0; }
    cudaLaunchConfig_t cfg = {};
    cfg.gridDim = dim3(CL * 16); cfg.blockDim = dim3(NTHREADS); cfg.dynamicSmemBytes = smem;
    cudaLaunchAttribute at[1];
    at[0].id = cudaLaunchAttributeClusterDimension; at[0].val.clusterDim.x = CL; at[0].val.clusterDim.y = 1; at[0].val.clusterDim.z = 1;
    cfg.attrs = at; cfg.numAttrs = 1;
    int n = 0;
    if (cudaOccupancyMaxActiveClusters(&n, mla_kernel<CL>, &cfg) != cudaSuccess) { cudaGetLastError(); return 0; }
    return n;
}

template <int CL> void launch(HostState& hs) {
    cudaLaunchConfig_t cfg = {};
    cfg.gridDim = dim3(hs.P.G); cfg.blockDim = dim3(NTHREADS); cfg.dynamicSmemBytes = hs.smem; cfg.stream = cudaStreamPerThread;
    cudaLaunchAttribute at[1];
    at[0].id = cudaLaunchAttributeClusterDimension; at[0].val.clusterDim.x = CL; at[0].val.clusterDim.y = 1; at[0].val.clusterDim.z = 1;
    cfg.attrs = at; cfg.numAttrs = 1;
    cudaLaunchKernelEx(&cfg, mla_kernel<CL>, hs.tm, hs.P);
}

void setup(HostState& hs, void* const* d_in, void* d_out) {
    for (int i = 0; i < 10; i++) hs.ptrs[i] = d_in[i];
    hs.P.x = (const __nv_bfloat16*)d_in[0];
    hs.P.out = (__nv_bfloat16*)d_out;
    hs.ready = true;
    hs.CL = 0;
    EncodeFn fn = nullptr;
    cudaDriverEntryPointQueryResult qr;
    if (cudaGetDriverEntryPoint("cuTensorMapEncodeTiled", (void**)&fn, cudaEnableDefault, &qr) != cudaSuccess || !fn) { cudaGetLastError(); return; }
    int n = max_clusters<8>();
    if (n > MAXG / 8) n = MAXG / 8;
    if (!plan(hs, 8, n)) return;
    hs.smem = SM<8>::END + 1024;
    bool ok = true;
    {
        const cuuint32_t kpg = 32;
        cuuint64_t dims[4] = {64, SK_, 16, 1}, st[3] = {DC_ * 2, 128, 128}; cuuint32_t box[4] = {64, kpg, 64 / kpg, 1};
        ok &= encode(fn, &hs.tm.m[1], d_in[1], dims, st, box, CU_TENSOR_MAP_SWIZZLE_128B);
    }
    for (int i = 0; i < 2; i++) {
        cuuint64_t dims[4] = {64, DC_, 4, H_}, st[3] = {H_ * D_ * 2, 128, D_ * 2}; cuuint32_t box[4] = {64, 16, 4, 1};
        ok &= encode(fn, &hs.tm.m[2 + i], d_in[3 + i], dims, st, box, CU_TENSOR_MAP_SWIZZLE_128B);
    }
    {
        cuuint64_t dims[4] = {64, H_ * D_, 7, 1}, st[3] = {M_ * 2, 128, 128}; cuuint32_t box[4] = {64, 8, 7, 1};
        ok &= encode(fn, &hs.tm.m[4], d_in[5], dims, st, box, CU_TENSOR_MAP_SWIZZLE_128B);
    }
    for (int i = 0; i < 2; i++) {
        cuuint64_t dims[4] = {F_, M_, 1, 1}, st[3] = {F_ * 2, 128, 128}; cuuint32_t box[4] = {16, 224, 1, 1};
        ok &= encode(fn, &hs.tm.m[5 + i], d_in[7 + i], dims, st, box, CU_TENSOR_MAP_SWIZZLE_32B);
    }
    {
        cuuint64_t dims[4] = {64, F_, 7, 1}, st[3] = {M_ * 2, 128, 128}; cuuint32_t box[4] = {64, 8, 7, 1};
        ok &= encode(fn, &hs.tm.m[7], d_in[9], dims, st, box, CU_TENSOR_MAP_SWIZZLE_128B);
    }
    {
        cuuint64_t dims[4] = {H_ * D_, M_, 1, 1}, st[3] = {H_ * D_ * 2, 128, 128}; cuuint32_t box[4] = {16, 224, 1, 1};
        ok &= encode(fn, &hs.tm.m[0], d_in[2], dims, st, box, CU_TENSOR_MAP_SWIZZLE_32B);
    }
    if (ok) hs.CL = 8;
}

}

extern "C" void kernel_launch(void* const* d_in, const int* in_sizes, int n_in, void* d_out, int out_size) {
    HostState& hs = g_hs;
    bool same = hs.ready && hs.P.out == d_out;
    for (int i = 0; same && i < 10; i++) same = hs.ptrs[i] == d_in[i];
    if (!same) setup(hs, d_in, d_out);
    if (hs.CL == 8) launch<8>(hs);
    else launch_fallback(d_in, d_out);
}
```

```cpp
#include <cuda_runtime.h>
#include <cuda_bf16.h>
#include <cuda.h>
#include <stdint.h>

namespace {

constexpr int H_ = 16, SK_ = 8192, D_ = 256, M_ = 448, DC_ = 1024, F_ = 1792;
constexpr int NWARPS = 12;
constexpr int NTHREADS = NWARPS * 32;
constexpr int NFCTA = 112;
constexpr int MAXNC = 16;
constexpr int MAXG = 128;
constexpr int MAXCH = 5;
constexpr int MAXUB = 10;
constexpr int MAXSLOT = 10;
constexpr int NSLOT = 20;
constexpr int MAXGR = 56;
#define MLA_WIN 5
#define MLA_WINC 6
constexpr int WIN = MLA_WIN;
#define MLA_KPRE 10
#define MLA_WINB 4
constexpr int WINB = MLA_WINB;
#define MLA_WIND 3
constexpr int WINC = MLA_WINC;
#define MLA_NINIT 4
constexpr int NINIT = MLA_NINIT;
constexpr float REF_SLACK = 20.f;
constexpr int SPIN_LIMIT = 1 << 15;

typedef unsigned long long u64;

constexpr int O_Q = 0;
constexpr int O_QA = O_Q + 2 * H_ * D_;
constexpr int O_CTX = O_QA + H_ * DC_ / 2;
constexpr int O_X1 = O_CTX + MAXSLOT * H_ * D_;
constexpr int O_X2 = O_X1 + 8 * 16 * 64;
constexpr int O_ACC = O_X2 + 8 * 16 * 64;
constexpr int O_ACTX = O_ACC + 2 * 8 * 64;
constexpr int O_PART = O_ACTX + H_ * D_;
constexpr int O_EPOCH = O_PART + MAXNC * H_ * DC_ / 2;
__device__ __align__(128) u64 g_s[O_EPOCH + 16];

struct Params {
    const __nv_bfloat16* x;
    __nv_bfloat16* out;
    int G, NC;
    int qB, rB, lB;
    int qE, rE, lE;
    int qK, rK;
    unsigned char firstB[H_];
    unsigned char nslot[H_];
};

struct Maps { CUtensorMap m[8]; };

__device__ __forceinline__ uint32_t smem_u32(const void* p) { return (uint32_t)__cvta_generic_to_shared(p); }
__device__ __forceinline__ void mbar_init(uint32_t bar, int cnt) { asm volatile("mbarrier.init.shared::cta.b64 [%0], %1;" ::"r"(bar), "r"(cnt) : "memory"); }
__device__ __forceinline__ void mbar_expect_tx(uint32_t bar, uint32_t bytes) { asm volatile("mbarrier.arrive.expect_tx.shared::cta.b64 _, [%0], %1;" ::"r"(bar), "r"(bytes) : "memory"); }
__device__ __forceinline__ void mbar_arrive(uint32_t bar) { asm volatile("mbarrier.arrive.shared::cta.b64 _, [%0];" ::"r"(bar) : "memory"); }
__device__ __forceinline__ bool mbar_try(uint32_t bar, uint32_t parity) {
    uint32_t ok;
    asm volatile("{\n.reg .pred p;\nmbarrier.try_wait.parity.shared::cta.b64 p, [%1], %2;\nselp.b32 %0, 1, 0, p;\n}\n" : "=r"(ok) : "r"(bar), "r"(parity) : "memory");
    return ok != 0;
}
__device__ __forceinline__ bool mbar_test(uint32_t bar) {
    uint32_t ok;
    asm volatile("{\n.reg .pred p;\nmbarrier.test_wait.parity.shared::cta.b64 p, [%1], 0;\nselp.b32 %0, 1, 0, p;\n}\n" : "=r"(ok) : "r"(bar) : "memory");
    return ok != 0;
}
__device__ __forceinline__ void mbar_wait_slow(uint32_t bar) {
    int lim = 0;
    while (!__all_sync(0xffffffffu, mbar_try(bar, 0)) && ++lim < SPIN_LIMIT) {}
}
__device__ __forceinline__ void mbar_wait(uint32_t bar) {
    if (!__all_sync(0xffffffffu, mbar_try(bar, 0))) mbar_wait_slow(bar);
}
__device__ __forceinline__ float ex2(float x) { float y; asm("ex2.approx.ftz.f32 %0, %1;" : "=f"(y) : "f"(x)); return y; }
__device__ __forceinline__ uint32_t mapa(uint32_t addr, uint32_t rank) {
    uint32_t r;
    asm volatile("mapa.shared::cluster.u32 %0, %1, %2;" : "=r"(r) : "r"(addr), "r"(rank));
    return r;
}
__device__ __forceinline__ void st_async_v4(uint32_t addr, uint32_t a, uint32_t b, uint32_t c, uint32_t d, uint32_t bar) {
    asm volatile("st.async.weak.shared::cluster.mbarrier::complete_tx::bytes.v4.b32 [%0], {%1,%2,%3,%4}, [%5];" ::"r"(addr), "r"(a), "r"(b), "r"(c), "r"(d), "r"(bar) : "memory");
}
__device__ __forceinline__ void st_async_v2(uint32_t addr, uint32_t a, uint32_t b, uint32_t bar) {
    asm volatile("st.async.weak.shared::cluster.mbarrier::complete_tx::bytes.v2.b32 [%0], {%1,%2}, [%3];" ::"r"(addr), "r"(a), "r"(b), "r"(bar) : "memory");
}
__device__ __forceinline__ void tma4d(uint32_t dst, const CUtensorMap* tm, int c0, int c1, int c2, int c3, uint32_t bar) {
    asm volatile("cp.async.bulk.tensor.4d.shared::cluster.global.mbarrier::complete_tx::bytes [%0], [%1, {%3, %4, %5, %6}], [%2];" ::"r"(dst), "l"(tm), "r"(bar), "r"(c0), "r"(c1), "r"(c2), "r"(c3) : "memory");
}
__device__ __forceinline__ void prefetch_tm(const CUtensorMap* tm) { asm volatile("prefetch.tensormap [%0];" ::"l"(tm) : "memory"); }
__device__ __forceinline__ void ldsm4(uint32_t (&r)[4], uint32_t addr) {
    asm volatile("ldmatrix.sync.aligned.m8n8.x4.shared.b16 {%0,%1,%2,%3}, [%4];" : "=r"(r[0]), "=r"(r[1]), "=r"(r[2]), "=r"(r[3]) : "r"(addr) : "memory");
}
__device__ __forceinline__ void ldsm4t(uint32_t (&r)[4], uint32_t addr) {
    asm volatile("ldmatrix.sync.aligned.m8n8.x4.trans.shared.b16 {%0,%1,%2,%3}, [%4];" : "=r"(r[0]), "=r"(r[1]), "=r"(r[2]), "=r"(r[3]) : "r"(addr) : "memory");
}
__device__ __forceinline__ void mma16816(float (&c)[4], const uint32_t (&a)[4], uint32_t b0, uint32_t b1) {
    asm volatile("mma.sync.aligned.m16n8k16.row.col.f32.bf16.bf16.f32 {%0,%1,%2,%3}, {%4,%5,%6,%7}, {%8,%9}, {%0,%1,%2,%3};"
                 : "+f"(c[0]), "+f"(c[1]), "+f"(c[2]), "+f"(c[3])
                 : "r"(a[0]), "r"(a[1]), "r"(a[2]), "r"(a[3]), "r"(b0), "r"(b1));
}
__device__ __forceinline__ uint32_t lds32(uint32_t addr) { uint32_t v; asm volatile("ld.shared.b32 %0, [%1];" : "=r"(v) : "r"(addr) : "memory"); return v; }
__device__ __forceinline__ uint4 lds128(uint32_t addr) { uint4 v; asm volatile("ld.shared.v4.b32 {%0,%1,%2,%3}, [%4];" : "=r"(v.x), "=r"(v.y), "=r"(v.z), "=r"(v.w) : "r"(addr) : "memory"); return v; }
__device__ __forceinline__ void bar_compute() { asm volatile("bar.sync 1, 256;" ::: "memory"); }
__device__ __forceinline__ void cluster_wait() { asm volatile("barrier.cluster.wait.acquire.aligned;" ::: "memory"); }

#define GS(off) (g_s + (uint32_t)(off))
__device__ __forceinline__ u64 mk(uint32_t payload, uint32_t tag) { return ((u64)tag << 32) | payload; }
__device__ __forceinline__ u64 mkf(float v, uint32_t tag) { return mk(__float_as_uint(v), tag); }
__device__ __forceinline__ void st_tag1(u64* p, u64 a) { asm volatile("st.relaxed.gpu.global.b64 [%0], %1;" ::"l"(p), "l"(a) : "memory"); }
__device__ __forceinline__ void st_tag2(u64* p, u64 a, u64 b) { asm volatile("st.relaxed.gpu.global.v2.b64 [%0], {%1,%2};" ::"l"(p), "l"(a), "l"(b) : "memory"); }
__device__ __forceinline__ void ld_tag2(const u64* p, u64& a, u64& b) { asm volatile("ld.relaxed.gpu.global.v2.b64 {%0,%1}, [%2];" : "=l"(a), "=l"(b) : "l"(p) : "memory"); }
__device__ __forceinline__ bool tag_ok(u64 a, u64 b, uint32_t tag) { return ((((uint32_t)(a >> 32) ^ tag) | ((uint32_t)(b >> 32) ^ tag)) & 0xffffu) == 0u; }
__device__ __forceinline__ void spin_clks(int n) { const long long c = clock64(); while (clock64() - c < n) {} }
#define MLA_DELAY 300
__device__ __forceinline__ float lo_f(u64 a) { return __uint_as_float((uint32_t)a); }

__device__ __forceinline__ u64 acc_enc(float v) {
    return (1ull << 59) + (1ull << 49) + (fabsf(v) < 33554432.f ? (u64)__float2ll_rn(v * 16777216.f) : (1ull << 54));
}
__device__ __forceinline__ int acc_cnt(u64 w) { return (int)(w >> 59); }
__device__ __forceinline__ bool acc_ovf(u64 w) { return ((w >> 54) & 31) != 0; }
__device__ __forceinline__ float acc_val(u64 w) { return (float)((long long)(w & ((1ull << 54) - 1)) - ((long long)(w >> 59) << 49)) * (1.f / 16777216.f); }
__device__ __forceinline__ void red_add(u64* p, u64 v) { asm volatile("red.relaxed.gpu.global.add.u64 [%0], %1;" ::"l"(p), "l"(v) : "memory"); }
__device__ __forceinline__ u64 atom_add(u64* p, u64 v) { u64 o; asm volatile("atom.relaxed.gpu.global.add.u64 %0, [%1], %2;" : "=l"(o) : "l"(p), "l"(v) : "memory"); return o; }
__device__ __forceinline__ void acc_wait(const u64* p, int n, u64& a, u64& b) {
    int lim = 0;
    while (!__all_sync(0xffffffffu, acc_cnt(a) == n && acc_cnt(b) == n) && ++lim < SPIN_LIMIT) { if (n > 0) ld_tag2(p, a, b); }
}

__device__ __forceinline__ uint32_t pack_bf16(float lo, float hi) {
    __nv_bfloat162 v = __floats2bfloat162_rn(lo, hi);
    return *reinterpret_cast<uint32_t*>(&v);
}
__device__ __forceinline__ float bf_lo(uint32_t w) { return __uint_as_float(w << 16); }
__device__ __forceinline__ float bf_hi(uint32_t w) { return __uint_as_float(w & 0xffff0000u); }
__device__ __forceinline__ void split2(float a, float b, uint32_t& hi, uint32_t& lo) {
    hi = pack_bf16(a, b);
    lo = pack_bf16(a - bf_lo(hi), b - bf_hi(hi));
}
__device__ __forceinline__ float wsum(float v) {
#pragma unroll
    for (int o = 16; o > 0; o >>= 1) v += __shfl_xor_sync(0xffffffffu, v, o);
    return v;
}

template <int N, int stride>
__device__ __forceinline__ void poll_pairs(const u64* base, int n, u64 (&a)[N], u64 (&b)[N], uint32_t tag) {
    const u64 ok = (u64)tag << 32;
#pragma unroll
    for (int i = 0; i < N; i++) { a[i] = i < n ? 0ull : ok; b[i] = a[i]; }
    int lim = 0;
    while (true) {
#pragma unroll
        for (int i = 0; i < N; i++) if (!tag_ok(a[i], b[i], tag)) ld_tag2(base + i * stride, a[i], b[i]);
        bool all = true;
#pragma unroll
        for (int i = 0; i < N; i++) all = all && tag_ok(a[i], b[i], tag);
        if (__all_sync(0xffffffffu, all) || ++lim > SPIN_LIMIT) break;
    }
}
__device__ __noinline__ float2 sum_copies(const u64* base, int stride, int n, uint32_t tag) {
    float2 v = make_float2(0.f, 0.f);
    for (int i = 0; i < n; i++) {
        u64 a, b; int lim = 0;
        do { ld_tag2(base + (size_t)i * stride, a, b); } while (!tag_ok(a, b, tag) && ++lim < SPIN_LIMIT);
        v.x += lo_f(a); v.y += lo_f(b);
    }
    return v;
}

#define TSTAMP(i) do {} while (0)
#define TSTAMP2(i) do {} while (0)

template <int CL> struct SM {
    static constexpr int W = DC_ / CL;
    static constexpr int QA_PITCH = W * 2 + 16;
    static constexpr int VBD_PITCH = MAXUB * 32 + 16;
    static constexpr int RING = 0;
    static constexpr int BARS = NSLOT * 8192;
    static constexpr int PART = BARS + 768;
    static constexpr int PBUF = PART + 16384;
    static constexpr int PML = PBUF + MAXCH * CL * 512;
    static constexpr int QA = PML + MAXCH * CL * 128;
    static constexpr int VBQ = QA + 16 * QA_PITCH;
    static constexpr int VBD = VBQ + 4 * 528;
    static constexpr int VBE = VBD + 4 * VBD_PITCH;
    static constexpr int VBF = VBE + 2 * 144;
    static constexpr int RED = VBF + 2 * 928;
    static constexpr int STAT = RED + 8 * 64 * 4;
    static constexpr int XS = STAT + 128;
    static constexpr int TAB = XS + 896;
    static constexpr int RS = TAB + 512;
    static constexpr int END = RS + 4096;
};
enum { B_FULL = 0, B_REL = MAXGR, B_PART = B_REL + 7, B_P = B_PART + MAXCH, B_Q = B_P + MAXCH, B_QA, B_FAC, B_E, B_F2, B_X,
       GO_Q, GO_QA, B_RS1, GO_CTX, B_RS2, GO_D, B_COUNT };
static_assert(B_COUNT <= 96, "barrier area");

template <int CL>
__global__ void __launch_bounds__(NTHREADS, 1)
mla_kernel(const __grid_constant__ Maps TM, const __grid_constant__ Params P) {
    typedef SM<CL> S;
    constexpr int W = S::W;
    constexpr int KPG = CL * 4;
    constexpr int TPG = KPG / 16;
    extern __shared__ unsigned char smem_raw[];
    const uint32_t sb = (smem_u32(smem_raw) + 1023u) & ~1023u;
    unsigned char* const sp = smem_raw + (sb - smem_u32(smem_raw));
    const int tid = threadIdx.x, warp = tid >> 5, lane = tid & 31;
    const int g = lane >> 2, t = lane & 3;
    const int b = blockIdx.x, NC = P.NC;
    const int rank = b % CL, cid = b / CL;
    auto BAR = [&](int i) { return sb + S::BARS + 8u * i; };
    auto SLOTI = [&](int gr) { return gr >= 2 * NSLOT ? gr - 2 * NSLOT : (gr >= NSLOT ? gr - NSLOT : gr); };
    auto SLOT = [&](int gr) { return sb + S::RING + (uint32_t)SLOTI(gr) * 8192u; };
    auto WAITG = [&](int gr) { mbar_wait(BAR(B_FULL + gr)); };

    const int uB0 = b * P.qB + min(max(b - P.lB, 0), P.rB), nB = P.qB + (b >= P.lB && b < P.lB + P.rB);
    const int h1 = uB0 >> 6, h2 = (uB0 + nB - 1) >> 6;
    const int uE0 = b * P.qE + min(max(b - P.lE, 0), P.rE), nE = P.qE + (b >= P.lE && b < P.lE + P.rE);
    const int nKG = P.qK + (cid < P.rK);
    const int T = nKG * TPG;
    const int NCH = (nKG + 3) >> 2;
    const bool isF = b < NFCTA;
    const int G_UK = nE, G_C = G_UK + nB, G_UV = G_C + nKG, G_WO = G_UV + nB, G_FG = G_WO + nE, G_WD = G_FG + 4, NGR = isF ? G_WD + 2 : G_FG;

    TSTAMP(0);
    if (warp == 9) {
        if (lane == 0) {
            prefetch_tm(&TM.m[0]); prefetch_tm(&TM.m[2]);
#pragma unroll
            for (int i = 0; i < NINIT; i++) mbar_init(BAR(B_FULL + i), 1);
            mbar_init(BAR(B_X), 1);
            asm volatile("fence.mbarrier_init.release.cluster;" ::: "memory");
            asm volatile("fence.proxy.async.shared::cta;" ::: "memory");
            mbar_expect_tx(BAR(B_X), 896);
            asm volatile("cp.async.bulk.shared::cluster.global.mbarrier::complete_tx::bytes [%0], [%1], %2, [%3];" ::"r"(sb + S::XS), "l"(P.x), "r"(896), "r"(BAR(B_X)) : "memory");
#pragma unroll
            for (int i = 0; i < NINIT; i++) {
                if (i < 4 || i < nE) {
                    mbar_expect_tx(BAR(B_FULL + i), 7168);
                    tma4d(sb + S::RING + i * 8192, &TM.m[0], ((uE0 + i) >> 1) * 16, ((uE0 + i) & 1) * 224, 0, 0, BAR(B_FULL + i));
                } else {
                    const int u = uB0 + i - nE;
                    mbar_expect_tx(BAR(B_FULL + i), 8192);
                    tma4d(sb + S::RING + i * 8192, &TM.m[2], 0, (u & 63) * 16, 0, u >> 6, BAR(B_FULL + i));
                }
            }
        }
        if (lane == 1) {
#pragma unroll
            for (int i = 1; i < 8; i++) prefetch_tm(&TM.m[i]);
        }
        __syncwarp();
        TSTAMP(22);
        __syncthreads();
        asm volatile("barrier.cluster.arrive.relaxed.aligned;" ::: "memory");
        {
            const uint32_t m0 = (lds32(sb + S::TAB + lane * 8 + 4) >> 16) & 255, m1 = (lds32(sb + S::TAB + lane * 8 + 260) >> 16) & 255;
            if (lane >= NINIT) mbar_expect_tx(BAR(B_FULL + lane), (m0 >= 1 && m0 <= 3) ? 8192 : 7168);
            if (lane + 32 < NGR) mbar_expect_tx(BAR(B_FULL + lane + 32), (m1 >= 1 && m1 <= 3) ? 8192 : 7168);
        }
        __syncwarp();
        TSTAMP(17);
        int next = NINIT, mine = lane < NINIT ? lane : -1, rel_ok = 0, lim = 0;
#pragma unroll 1
        while (next < NGR && ++lim < (SPIN_LIMIT << 6)) {
            const int wflag = *reinterpret_cast<volatile int*>(sp + S::STAT + 16);
            const int win = next >= G_WO ? MLA_WIND : wflag;
            const bool fin = mine < 0 || mbar_test(BAR(B_FULL + mine));
            if (fin) mine = -1;
            const unsigned busy = __ballot_sync(0xffffffffu, !fin);
            if (__popc(busy) >= win) continue;
            const uint2 e = *reinterpret_cast<const uint2*>(sp + S::TAB + next * 8);
            const int need = e.y >> 24;
            if (need > rel_ok) { if (!__all_sync(0xffffffffu, mbar_test(BAR(B_REL + need - 1)))) continue; rel_ok = need; }
            if (lane == __ffs(~busy) - 1) {
                tma4d(SLOT(next), &TM.m[(e.y >> 16) & 255], e.x & 0xffff, e.x >> 16, e.y & 255, (e.y >> 8) & 255, BAR(B_FULL + next));
                mine = next;
            }
            __syncwarp();
            next++;
        }
        TSTAMP(18);
        cluster_wait();
        return;
    }

    if (tid == 0) {
#pragma unroll
        for (int i = NINIT; i < 30; i++) mbar_init(BAR(B_FULL + i), 1);
        asm volatile("fence.mbarrier_init.release.cluster;" ::: "memory");
        asm volatile("fence.proxy.async.shared::cta;" ::: "memory");
    } else if (tid == 64) {
#pragma unroll
        for (int i = 30; i < B_REL; i++) mbar_init(BAR(B_FULL + i), 1);
        asm volatile("fence.mbarrier_init.release.cluster;" ::: "memory");
        asm volatile("fence.proxy.async.shared::cta;" ::: "memory");
    } else if (tid == 320) {
#pragma unroll
        for (int i = B_REL; i < B_PART; i++) mbar_init(BAR(i), 8);
#pragma unroll
        for (int i = B_PART; i < B_Q; i++) mbar_init(BAR(i), 1);
        asm volatile("fence.mbarrier_init.release.cluster;" ::: "memory");
    } else if (tid == 352) {
#pragma unroll
        for (int i = B_Q; i < B_COUNT; i++) if (i != B_X) mbar_init(BAR(i), 1);
        asm volatile("fence.mbarrier_init.release.cluster;" ::: "memory");
    }
    uint32_t tag;
    {
        const unsigned* ep;
        asm volatile("mov.u64 %0, %1;" : "=l"(ep) : "l"(g_s + O_EPOCH));
        asm volatile("ld.relaxed.gpu.global.u32 %0, [%1];" : "=r"(tag) : "l"(ep) : "memory");
    }
    if (warp == 1) {
            if (lane == 0) *reinterpret_cast<volatile int*>(sp + S::STAT + 16) = WIN;
#pragma unroll
            for (int k = 0; k < 2; k++) {
                const int gr = lane + 32 * k;
                int c0 = 0, c1, c2 = 0, c3 = 0, mp;
                if (gr < G_UK) { const int u = uE0 + gr; mp = 0; c0 = (u >> 1) * 16; c1 = (u & 1) * 224; }
                else if (gr < G_C) { const int u = uB0 + gr - G_UK; mp = 2; c1 = (u & 63) * 16; c3 = u >> 6; }
                else if (gr < G_UV) { mp = 1; c1 = ((gr - G_C) * NC + cid) * KPG; c2 = rank * (W / 64); }
                else if (gr < G_WO) { const int u = uB0 + gr - G_UV; mp = 3; c1 = (u & 63) * 16; c3 = u >> 6; }
                else if (gr < G_FG) { mp = 4; c1 = (uE0 + gr - G_WO) * 8; }
                else if (gr < G_WD) { const int i = gr - G_FG; mp = 5 + (i >> 1); c0 = b * 16; c1 = (i & 1) * 224; }
                else { mp = 7; c1 = b * 16 + (gr - G_WD) * 8; }
                const int pg = gr - NSLOT;
                const int rl = pg < 0 ? -1 : (pg < G_C ? 0 : (pg < G_UV ? 1 + ((pg - G_C) >> 2) : 6));
                *reinterpret_cast<uint2*>(sp + S::TAB + gr * 8) = make_uint2((uint32_t)c0 | ((uint32_t)c1 << 16), (uint32_t)c2 | ((uint32_t)c3 << 8) | ((uint32_t)mp << 16) | ((uint32_t)(rl + 1) << 24));
            }
    } else if (warp == 8) {
        for (int i = lane; i < nE * 8; i += 32) { const int u = uE0 + (i >> 3); st_tag2(GS(O_Q + (u & 1) * (H_ * D_) + (u >> 1) * 16 + (i & 7) * 2), 0ull, 0ull); }
        for (int i = lane; i < nB * 4; i += 32) st_tag2(GS(O_QA + uB0 * 8 + i * 2), 0ull, 0ull);
    }
    __syncthreads();
    asm volatile("barrier.cluster.arrive.relaxed.aligned;" ::: "memory");
    asm volatile("" : "+r"(tag));
    tag += 1u;

    auto recv_ctxl = [&](int th) {
        const int d_it = th >> 2, d_q = th & 3;
        const bool d_act = d_it < nB * 4;
        const int d_u = uB0 + (d_it >> 2);
        const u64* d_ptr = GS(O_PART + d_q * (H_ * DC_ / 2) + (d_act ? d_u * 8 + (d_it & 3) * 2 : 0));
        const int d_n = d_act ? ((NC - d_q + 3) >> 2) : 0;
        const int hp = d_act && (d_u >> 6) != h1;
        u64 a[4], bb[4];
        mbar_wait(BAR(GO_D));
        spin_clks(MLA_DELAY);
        poll_pairs<4, 4 * H_ * DC_ / 2>(d_ptr, d_n, a, bb, tag);
        float w[4], m = -INFINITY;
#pragma unroll
        for (int i = 0; i < 4; i++) {
            w[i] = i < d_n ? __uint_as_float(((uint32_t)(a[i] >> 32) & 0xffff0000u) | (uint32_t)(bb[i] >> 48)) : -INFINITY;
            m = fmaxf(m, w[i]);
        }
        m = fmaxf(m, __shfl_xor_sync(0xffffffffu, m, 1));
        m = fmaxf(m, __shfl_xor_sync(0xffffffffu, m, 2));
        if (!d_act) m = 0.f;
        float v0 = 0.f, v1 = 0.f, v2 = 0.f, v3 = 0.f, den = 0.f;
#pragma unroll
        for (int i = 0; i < 4; i++) {
            const float e = ex2(w[i] - m);
            den += e; v0 += e * bf_lo((uint32_t)a[i]); v1 += e * bf_hi((uint32_t)a[i]); v2 += e * bf_lo((uint32_t)bb[i]); v3 += e * bf_hi((uint32_t)bb[i]);
        }
#pragma unroll
        for (int o = 1; o < 4; o <<= 1) {
            v0 += __shfl_xor_sync(0xffffffffu, v0, o); v1 += __shfl_xor_sync(0xffffffffu, v1, o); v2 += __shfl_xor_sync(0xffffffffu, v2, o);
            v3 += __shfl_xor_sync(0xffffffffu, v3, o); den += __shfl_xor_sync(0xffffffffu, den, o);
        }
        const float inv = __fdividef(1.f, den);
        uint32_t hiA, loA, hiB, loB;
        split2(v0 * inv, v1 * inv, hiA, loA); split2(v2 * inv, v3 * inv, hiB, loB);
        const bool mine = d_act && hp == (d_q >> 1);
        *reinterpret_cast<uint2*>(sp + S::VBD + (d_it * 4 + d_q) * 8) = mine ? ((d_q & 1) ? make_uint2(loA, loB) : make_uint2(hiA, hiB)) : make_uint2(0u, 0u);
    };

    if (warp == 8) {
        uint32_t rpb[CL];
#pragma unroll
        for (int dst = 0; dst < CL; dst++) rpb[dst] = mapa(sb, dst);
        const uint32_t rml0 = mapa(sb, t % CL), rml1 = mapa(sb, (t + 4) % CL);
        if (lane < NCH) {
            const int nt = min(CL, T - lane * CL);
            if (lane * CL + rank < T) mbar_expect_tx(BAR(B_PART + lane), 8192);
            mbar_expect_tx(BAR(B_P + lane), nt * 640);
        }
        cluster_wait();
        float Rlo = -INFINITY, Rhi = -INFINITY;
        for (int j = 0; j < NCH; j++) {
            if (j * CL + rank >= T) break;
            if (j > 0) {
                const int jp = j == 1 ? 0 : j - 2 + (j == 2);
                if (j != 2) {
                    mbar_wait(BAR(B_P + jp));
                    float nlo = -INFINITY, nhi = -INFINITY;
#pragma unroll
                    for (int tl = 0; tl < CL; tl++) {
                        const uint4 ml = lds128(sb + S::PML + (jp * CL + tl) * 128 + g * 16);
                        nlo = fmaxf(nlo, __uint_as_float(ml.x)); nhi = fmaxf(nhi, __uint_as_float(ml.z));
                    }
                    Rlo = nlo > Rlo + REF_SLACK ? nlo : Rlo; Rhi = nhi > Rhi + REF_SLACK ? nhi : Rhi;
                }
            }
            const uint32_t pa = sb + S::PART + (j & 1) * 8192 + lane * 16;
            const uint32_t opb = S::PBUF + (j * CL + rank) * 512 + lane * 16;
            const uint32_t opm = S::PML + (j * CL + rank) * 128 + g * 16;
            const uint32_t obar = S::BARS + 8 * (B_P + j);
            mbar_wait(BAR(B_PART + j));

            uint4 v0[8], v1[8];
#pragma unroll
            for (int src = 0; src < 8; src++) { v0[src] = lds128(pa + src * 1024); v1[src] = lds128(pa + src * 1024 + 512); }
#define SUM8(V, F) (((__uint_as_float(V[0].F) + __uint_as_float(V[1].F)) + (__uint_as_float(V[2].F) + __uint_as_float(V[3].F))) + \
                    ((__uint_as_float(V[4].F) + __uint_as_float(V[5].F)) + (__uint_as_float(V[6].F) + __uint_as_float(V[7].F))))
            const float s00 = SUM8(v0, x), s01 = SUM8(v0, y), s02 = SUM8(v0, z), s03 = SUM8(v0, w);
            const float s10 = SUM8(v1, x), s11 = SUM8(v1, y), s12 = SUM8(v1, z), s13 = SUM8(v1, w);
#undef SUM8

            float mlo = fmaxf(fmaxf(s00, s01), fmaxf(s10, s11));
            float mhi = fmaxf(fmaxf(s02, s03), fmaxf(s12, s13));
            mlo = fmaxf(mlo, __shfl_xor_sync(0xffffffffu, mlo, 1)); mhi = fmaxf(mhi, __shfl_xor_sync(0xffffffffu, mhi, 1));
            mlo = fmaxf(mlo, __shfl_xor_sync(0xffffffffu, mlo, 2)); mhi = fmaxf(mhi, __shfl_xor_sync(0xffffffffu, mhi, 2));

            mlo = mlo > Rlo + REF_SLACK ? mlo : Rlo; mhi = mhi > Rhi + REF_SLACK ? mhi : Rhi;
            const uint32_t a0 = pack_bf16(ex2(s00 - mlo), ex2(s01 - mlo));
            const uint32_t a1 = pack_bf16(ex2(s02 - mhi), ex2(s03 - mhi));
            const uint32_t a2 = pack_bf16(ex2(s10 - mlo), ex2(s11 - mlo));
            const uint32_t a3 = pack_bf16(ex2(s12 - mhi), ex2(s13 - mhi));
#pragma unroll
            for (int dst = 0; dst < CL; dst++) st_async_v4(rpb[dst] + opb, a0, a1, a2, a3, rpb[dst] + obar);

            float llo = (bf_lo(a0) + bf_hi(a0)) + (bf_lo(a2) + bf_hi(a2));
            float lhi = (bf_lo(a1) + bf_hi(a1)) + (bf_lo(a3) + bf_hi(a3));
            llo += __shfl_xor_sync(0xffffffffu, llo, 1); lhi += __shfl_xor_sync(0xffffffffu, lhi, 1);
            llo += __shfl_xor_sync(0xffffffffu, llo, 2); lhi += __shfl_xor_sync(0xffffffffu, lhi, 2);
            st_async_v4(rml0 + opm, __float_as_uint(mlo), __float_as_uint(llo), __float_as_uint(mhi), __float_as_uint(lhi), rml0 + obar);
            if (CL == 8) st_async_v4(rml1 + opm, __float_as_uint(mlo), __float_as_uint(llo), __float_as_uint(mhi), __float_as_uint(lhi), rml1 + obar);
        }
        recv_ctxl(128 + lane);
        asm volatile("bar.arrive 2, 288;" ::: "memory");
    } else if (warp == 10) {
        const int row = uE0 * 8 + lane * 2;
        const bool rowact = lane < nE * 4;
        const int ns = rowact ? P.nslot[row >> 8] : 0;
        const u64* cp = GS(O_CTX + (rowact ? row : 0));
        const int nq = h2 != h1 ? 8 : 4;
        cluster_wait();
        {
            mbar_wait(BAR(GO_Q));
            if (rowact) st_tag2(GS(O_ACTX + row), 0ull, 0ull);
            spin_clks(MLA_DELAY);
            u64 a[8], bb[8], a2[8], b2[8];
            poll_pairs<8, 64>(GS(O_Q + h1 * D_ + lane * 2), nq, a, bb, tag);
            poll_pairs<8, 64>(GS(O_Q + H_ * D_ + h1 * D_ + lane * 2), nq, a2, b2, tag);
#pragma unroll
            for (int i = 0; i < 8; i++) {
                uint32_t hi, lo;
                const int o = S::VBQ + (i >> 2) * 2 * 528 + ((i & 3) * 32 + lane) * 4;
                split2(lo_f(a[i]) + lo_f(a2[i]), lo_f(bb[i]) + lo_f(b2[i]), hi, lo);
                *reinterpret_cast<uint32_t*>(sp + o) = hi; *reinterpret_cast<uint32_t*>(sp + o + 528) = lo;
            }
            __syncwarp();
            if (lane == 0) mbar_arrive(BAR(B_Q));
            TSTAMP(11);
        }
        {
            mbar_wait(BAR(GO_CTX));
            TSTAMP(56);
            u64 w0 = 0ull, w1 = 0ull;
            acc_wait(GS(O_ACTX + (rowact ? row : 0)), ns, w0, w1);
            TSTAMP(57);
            float v0 = acc_val(w0), v1 = acc_val(w1);
            if (acc_ovf(w0) || acc_ovf(w1)) { const float2 v = sum_copies(cp, H_ * D_, ns, tag); v0 = v.x; v1 = v.y; }
            __syncwarp();
            uint32_t hi, lo; split2(v0, v1, hi, lo);
            *reinterpret_cast<uint32_t*>(sp + S::VBE + lane * 4) = hi;
            *reinterpret_cast<uint32_t*>(sp + S::VBE + 144 + lane * 4) = lo;
            __syncwarp();
            if (lane == 0) mbar_arrive(BAR(B_E));
            TSTAMP(12);
        }
    } else if (warp == 11) {
        const int half = lane & 1;
        const bool own = rank < 7;
        const int col = (own ? rank * 64 : 0) + (lane >> 3) * 16 + (lane & 7);
        u64* x1d = GS(O_X1 + (rank * 16 + cid) * 64 + lane * 2);
        u64* x2d = GS(O_X2 + (rank * 16 + cid) * 64 + lane * 2);
        u64* ap1 = GS(O_ACC + rank * 64 + lane * 2);
        if (lane == 0) {
            if (own) { mbar_expect_tx(BAR(B_RS1), 2048); if (isF) mbar_expect_tx(BAR(B_RS2), 2048); }
            if (isF) { mbar_expect_tx(BAR(B_FAC), 7 * 256); mbar_expect_tx(BAR(B_F2), 7 * 8); }
        }
        mbar_wait(BAR(B_X));
        const float x0 = __bfloat162float(*reinterpret_cast<const __nv_bfloat16*>(sp + S::XS + col * 2));
        const float x1 = __bfloat162float(*reinterpret_cast<const __nv_bfloat16*>(sp + S::XS + col * 2 + 16));
        float piv = 0.f;
#pragma unroll
        for (int i = 0; i < 7; i++) { const uint32_t w = lds32(sb + S::XS + (i * 32 + lane) * 4); piv += bf_lo(w) + bf_hi(w); }
        piv = wsum(piv) * (1.f / M_);
        constexpr int NB = W / 128;
        const u64* qp = GS(O_QA + rank * (W / 2) + lane * 2);
        cluster_wait();
        {
            mbar_wait(BAR(GO_Q));
            if (own && cid == 0) { st_tag2(ap1, 0ull, 0ull); st_tag2(ap1 + 8 * 64, 0ull, 0ull); }
            mbar_wait(BAR(GO_QA)); spin_clks(MLA_DELAY);
#pragma unroll
            for (int bt = 0; bt < NB; bt++) {
                u64 a[16], bb[16];
                poll_pairs<16, DC_ / 2>(qp + bt * 64, 16, a, bb, tag);
#pragma unroll
                for (int i = 0; i < 16; i++)
                    *reinterpret_cast<uint2*>(sp + S::QA + i * S::QA_PITCH + (bt * 32 + lane) * 8) = make_uint2((uint32_t)a[i], (uint32_t)bb[i]);
            }
            __syncwarp();
            if (lane == 0) { mbar_arrive(BAR(B_QA)); *reinterpret_cast<volatile int*>(sp + S::STAT + 16) = WINC; }
            TSTAMP(15);
        }
        if (own) {
            float hv0 = 0.f, hv1 = 0.f;
            {
                uint32_t rvb[CL];
#pragma unroll
                for (int d = 0; d < CL; d++) rvb[d] = mapa(sb, d);
                const uint32_t vo = S::VBF + (((rank * 4 + (lane >> 3)) * 4 + ((lane & 7) >> 1)) * 2 + half) * 8;
                mbar_wait(BAR(B_RS1));
                TSTAMP(52);
                float2 p[8];
#pragma unroll
                for (int i = 0; i < 8; i++) p[i] = *reinterpret_cast<const float2*>(sp + S::RS + i * 256 + lane * 8);
                const float s0 = ((p[0].x + p[1].x) + (p[2].x + p[3].x)) + ((p[4].x + p[5].x) + (p[6].x + p[7].x));
                const float s1 = ((p[0].y + p[1].y) + (p[2].y + p[3].y)) + ((p[4].y + p[5].y) + (p[6].y + p[7].y));
                const u64 e0 = acc_enc(s0), e1 = acc_enc(s1);
                u64 w0 = atom_add(ap1, e0), w1 = atom_add(ap1 + 1, e1);
                st_tag2(x1d, mkf(s0, tag), mkf(s1, tag));
                TSTAMP(53);
                if (isF) {
                    w0 += e0; w1 += e1;
                    acc_wait(ap1, NC, w0, w1);
                    float v0 = acc_val(w0), v1 = acc_val(w1);
                    if (acc_ovf(w0) || acc_ovf(w1)) { const float2 v = sum_copies(GS(O_X1 + rank * 16 * 64 + lane * 2), 64, NC, tag); v0 = v.x; v1 = v.y; }
                    __syncwarp();
                    hv0 = x0 + v0; hv1 = x1 + v1;
                    const float o0 = __shfl_xor_sync(0xffffffffu, hv0, 1), o1 = __shfl_xor_sync(0xffffffffu, hv1, 1);
                    uint32_t hiA, loA, hiB, loB;
                    split2((half ? o0 : hv0) - piv, (half ? hv0 : o0) - piv, hiA, loA);
                    split2((half ? o1 : hv1) - piv, (half ? hv1 : o1) - piv, hiB, loB);
#pragma unroll
                    for (int d = 0; d < CL; d++) st_async_v2(rvb[d] + vo, half ? loA : hiA, half ? loB : hiB, rvb[d] + S::BARS + 8 * B_FAC);
                    TSTAMP(13);
                    const float d0 = hv0 - piv, d1 = hv1 - piv;
                    float s1 = d0 + d1, s2 = d0 * d0 + d1 * d1;
#pragma unroll
                    for (int o = 16; o > 0; o >>= 1) { s1 += __shfl_xor_sync(0xffffffffu, s1, o); s2 += __shfl_xor_sync(0xffffffffu, s2, o); }
                    if (lane < CL) { const uint32_t rb = mapa(sb, lane); st_async_v2(rb + S::STAT + 64 + rank * 8, __float_as_uint(s1), __float_as_uint(s2), rb + S::BARS + 8 * B_F2); }
                }
            }
            if (isF) {
                mbar_wait(BAR(B_RS2));
                TSTAMP(54);
                float2 p[8];
#pragma unroll
                for (int i = 0; i < 8; i++) p[i] = *reinterpret_cast<const float2*>(sp + S::RS + 2048 + i * 256 + lane * 8);
                const float s0 = ((p[0].x + p[1].x) + (p[2].x + p[3].x)) + ((p[4].x + p[5].x) + (p[6].x + p[7].x));
                const float s1 = ((p[0].y + p[1].y) + (p[2].y + p[3].y)) + ((p[4].y + p[5].y) + (p[6].y + p[7].y));
                constexpr int NFC = NFCTA / CL;
                u64 enc[2], old[2];
                enc[0] = acc_enc(s0); enc[1] = acc_enc(s1);
                old[0] = atom_add(ap1 + 8 * 64, enc[0]); old[1] = atom_add(ap1 + 8 * 64 + 1, enc[1]);
                st_tag2(x2d, mkf(s0, tag), mkf(s1, tag));
                if (b == 0 && lane == 0) asm volatile("st.relaxed.gpu.global.u32 [%0], %1;" ::"l"(g_s + O_EPOCH), "r"(tag == 65535u ? 0u : tag) : "memory");
#pragma unroll
                for (int k = 0; k < 2; k++) {
                    const u64 tot = old[k] + enc[k];
                    if (acc_cnt(tot) == NFC) {
                        float v = acc_val(tot);
                        if (acc_ovf(tot)) { const float2 c = sum_copies(GS(O_X2 + rank * 16 * 64 + lane * 2), 64, NFC, tag); v = k ? c.y : c.x; }
                        P.out[col + 8 * k] = __float2bfloat16((k ? hv1 : hv0) + v);
                    }
                }
                TSTAMP(14);
            }
        }
    } else {
        const int mi = lane >> 3, r = lane & 7;
        if (warp < nE) {
            const int u = uE0 + warp;
            u64* dq = GS(O_Q + (u & 1) * (H_ * D_) + (u >> 1) * 16 + g);
            mbar_wait(BAR(B_X));
            uint32_t xw[7], bx[14][2];
#pragma unroll
            for (int i = 0; i < 7; i++) xw[i] = lds32(sb + S::XS + (i * 32 + lane) * 4);
#pragma unroll
            for (int ks = 0; ks < 14; ks++) {
                const uint32_t xa = sb + S::XS + ((u & 1) * 224 + ks * 16 + 2 * t) * 2;
                bx[ks][0] = lds32(xa); bx[ks][1] = lds32(xa + 16);
                if (g != 0) { bx[ks][0] = bx[ks][1] = g == 1 ? 0x3f803f80u : 0u; }
            }
            float s = 0.f;
#pragma unroll
            for (int i = 0; i < 7; i++) s += bf_lo(xw[i]) + bf_hi(xw[i]);
            const float mean = wsum(s) * (1.f / M_);
            float vs = 0.f;
#pragma unroll
            for (int i = 0; i < 7; i++) { const float d0 = bf_lo(xw[i]) - mean, d1 = bf_hi(xw[i]) - mean; vs += d0 * d0 + d1 * d1; }
            const float rstd = rsqrtf(wsum(vs) * (1.f / M_) + 1e-5f);
            float c[2][4];
#pragma unroll
            for (int i = 0; i < 2; i++) { c[i][0] = c[i][1] = c[i][2] = c[i][3] = 0.f; }
            const int rr = (mi >> 1) * 8 + r;
            const uint32_t wa = sb + S::RING + warp * 8192 + rr * 32 + ((((mi & 1) ^ (rr >> 2)) & 1) << 4);
            WAITG(warp);
#pragma unroll
            for (int ks = 0; ks < 14; ks++) {
                uint32_t a[4];
                ldsm4t(a, wa + ks * 512);
                mma16816(c[ks & 1], a, bx[ks][0], bx[ks][1]);
            }
            if (t == 0) {
                st_tag1(dq, mkf(((c[0][0] + c[1][0]) - mean * (c[0][1] + c[1][1])) * rstd, tag));
                st_tag1(dq + 8, mkf(((c[0][2] + c[1][2]) - mean * (c[0][3] + c[1][3])) * rstd, tag));
            }
            if (tid == 0) mbar_arrive(BAR(GO_Q));
            TSTAMP(1);
        }
        __syncwarp();
        cluster_wait();
        {
            mbar_wait(BAR(B_Q));
            uint32_t bq[16][2];
#pragma unroll
            for (int ks = 0; ks < 16; ks++) {
                bq[ks][0] = g < 4 ? lds32(sb + S::VBQ + g * 528 + (ks * 16 + 2 * t) * 2) : 0u;
                bq[ks][1] = g < 4 ? lds32(sb + S::VBQ + g * 528 + (ks * 16 + 2 * t + 8) * 2) : 0u;
            }
            TSTAMP(2);
            for (int un = warp; un < nB; un += 8) {
                WAITG(G_UK + un);
                const uint32_t rowa = sb + S::RING + (G_UK + un) * 8192 + ((mi & 1) * 8 + r) * 128;
                float c[4][4];
#pragma unroll
                for (int i = 0; i < 4; i++) { c[i][0] = c[i][1] = c[i][2] = c[i][3] = 0.f; }
#pragma unroll
                for (int ks = 0; ks < 16; ks++) {
                    uint32_t a[4];
                    const int ch = (ks & 3) * 2 + (mi >> 1);
                    ldsm4(a, rowa + (ks >> 2) * 2048 + ((ch ^ r) << 4));
                    mma16816(c[ks & 3], a, bq[ks][0], bq[ks][1]);
                }
                constexpr float SC = 0.0625f * 1.4426950408889634f;
                const float va = (((c[0][0] + c[1][0]) + (c[2][0] + c[3][0])) + ((c[0][1] + c[1][1]) + (c[2][1] + c[3][1]))) * SC;
                const float vb = (((c[0][2] + c[1][2]) + (c[2][2] + c[3][2])) + ((c[0][3] + c[1][3]) + (c[2][3] + c[3][3]))) * SC;
                const uint32_t wa = pack_bf16(va, __shfl_down_sync(0xffffffffu, va, 4));
                const uint32_t wb = pack_bf16(vb, __shfl_down_sync(0xffffffffu, vb, 4));
                const uint32_t wa2 = __shfl_down_sync(0xffffffffu, wa, 8), wb2 = __shfl_down_sync(0xffffffffu, wb, 8);
                const int u = uB0 + un;
                if (t == ((u >> 6) == h1 ? 0 : 1) && (g & 3) == 0) {
                    u64* dst = GS(O_QA + u * 8 + (g >> 1));
                    st_tag2(dst, mk(wa, tag), mk(wa2, tag));
                    st_tag2(dst + 4, mk(wb, tag), mk(wb2, tag));
                }
            }
            __syncwarp();
            if (lane == 0) mbar_arrive(BAR(B_REL + 0));
            if (tid == 0) { mbar_arrive(BAR(GO_QA)); *reinterpret_cast<volatile int*>(sp + S::STAT + 16) = WINB; }
            TSTAMP(3);

        }
        if (warp < 4) {
            const uint32_t pd0 = mapa(sb + S::PART + rank * 1024 + lane * 16, 2 * warp), pd1 = mapa(sb + S::PART + rank * 1024 + lane * 16, 2 * warp + 1);
            const uint32_t pb0 = mapa(BAR(B_PART), 2 * warp), pb1 = mapa(BAR(B_PART), 2 * warp + 1);
            const uint32_t sc_off = ((mi >> 1) * 8 + r) * 128;
            mbar_wait(BAR(B_QA));
            uint32_t qa[8][4];
#pragma unroll
            for (int ks = 0; ks < 8; ks++) {
                const uint32_t a = sb + S::QA + g * S::QA_PITCH + (ks * 16 + 2 * t) * 2;
                qa[ks][0] = lds32(a); qa[ks][1] = lds32(a + 8 * S::QA_PITCH); qa[ks][2] = lds32(a + 16); qa[ks][3] = lds32(a + 8 * S::QA_PITCH + 16);
            }
            TSTAMP(4);
#pragma unroll 1
            for (int j = 0; j < NCH; j++) {
                if (j * 4 + warp < nKG) {
                    const int gr = G_C + j * 4 + warp;
                    const uint32_t rowa = SLOT(gr) + sc_off;
                    WAITG(gr);
                    float s[4][4];
#pragma unroll
                    for (int i = 0; i < 4; i++) { s[i][0] = s[i][1] = s[i][2] = s[i][3] = 0.f; }
#pragma unroll
                    for (int ks = 0; ks < 8; ks++) {
                        uint32_t b0[4], b1[4];
                        const uint32_t ad = rowa + (ks >> 2) * 4096 + ((((ks & 3) * 2 + (mi & 1)) ^ r) << 4);
                        ldsm4(b0, ad); ldsm4(b1, ad + 2048);
                        mma16816(s[0], qa[ks], b0[0], b0[1]); mma16816(s[1], qa[ks], b0[2], b0[3]);
                        mma16816(s[2], qa[ks], b1[0], b1[1]); mma16816(s[3], qa[ks], b1[2], b1[3]);
                    }
                    if (j >= 2) mbar_wait(BAR(B_P + j - 2));
                    const uint32_t o = (j & 1) * 8192;
                    st_async_v4(pd0 + o, __float_as_uint(s[0][0]), __float_as_uint(s[0][1]), __float_as_uint(s[0][2]), __float_as_uint(s[0][3]), pb0 + 8 * j);
                    st_async_v4(pd0 + o + 512, __float_as_uint(s[1][0]), __float_as_uint(s[1][1]), __float_as_uint(s[1][2]), __float_as_uint(s[1][3]), pb0 + 8 * j);
                    st_async_v4(pd1 + o, __float_as_uint(s[2][0]), __float_as_uint(s[2][1]), __float_as_uint(s[2][2]), __float_as_uint(s[2][3]), pb1 + 8 * j);
                    st_async_v4(pd1 + o + 512, __float_as_uint(s[3][0]), __float_as_uint(s[3][1]), __float_as_uint(s[3][2]), __float_as_uint(s[3][3]), pb1 + 8 * j);
                    TSTAMP(24 + j);
                }
                if (lane == 0) mbar_arrive(BAR(B_REL + 1 + j));
            }
        } else {
            const int pw = warp - 4;
            const uint32_t pv_off = (pw >> 1) * 4096 + ((mi & 1) * 8 + r) * 128;
            const uint32_t c0 = ((((pw & 1) * 4 + (mi >> 1)) ^ r) << 4), c1 = ((((pw & 1) * 4 + 2 + (mi >> 1)) ^ r) << 4);
            u64* gp = GS(O_PART + (cid * H_ + g) * (DC_ / 2) + (rank * W + pw * 32) / 2 + 2 * t);
            mbar_wait(BAR(B_QA));
            st_tag2(gp, 0ull, 0ull); st_tag2(gp + 8, 0ull, 0ull); st_tag2(gp + 8 * (DC_ / 2), 0ull, 0ull); st_tag2(gp + 8 * (DC_ / 2) + 8, 0ull, 0ull);
            float acc[4][4], acc2[4][4];
#pragma unroll
            for (int i = 0; i < 4; i++) { acc[i][0] = acc[i][1] = acc[i][2] = acc[i][3] = 0.f; acc2[i][0] = acc2[i][1] = acc2[i][2] = acc2[i][3] = 0.f; }
            float Mlo = -INFINITY, Mhi = -INFINITY, Llo = 0.f, Lhi = 0.f;
#pragma unroll 1
            for (int j = 0; j < NCH; j++) {
                const int nt = min(CL, T - j * CL);
                const int g0 = G_C + j * 4;
                const uint32_t pml = sb + S::PML + j * CL * 128 + g * 16, ppb = sb + S::PBUF + j * CL * 512 + lane * 16;
                uint32_t va[4];
#pragma unroll
                for (int gi = 0; gi < 4; gi++) va[gi] = SLOT(g0 + (gi * 2 < nt ? gi : 0)) + pv_off;
                mbar_wait(BAR(B_P + j));
                if (warp == 4 && lane == 0) { TSTAMP2(32 + j); }
                float flo[CL], fhi[CL];
                bool stdref = true;
                {
                    uint4 ml[CL];
#pragma unroll
                    for (int tl = 0; tl < CL; tl++) ml[tl] = lds128(pml + (tl < nt ? tl : 0) * 128);
#pragma unroll
                    for (int tl = 0; tl < CL; tl++) stdref = stdref && __uint_as_float(ml[tl].x) == Mlo && __uint_as_float(ml[tl].z) == Mhi;
                    stdref = __all_sync(0xffffffffu, stdref);
                    if (stdref) {
#pragma unroll
                        for (int tl = 0; tl < CL; tl++) { Llo += tl < nt ? __uint_as_float(ml[tl].y) : 0.f; Lhi += tl < nt ? __uint_as_float(ml[tl].w) : 0.f; flo[tl] = fhi[tl] = 0.f; }
                    } else {
                        float nlo = Mlo, nhi = Mhi;
#pragma unroll
                        for (int tl = 0; tl < CL; tl++) {
                            if (tl >= nt) { ml[tl].x = 0xff800000u; ml[tl].z = 0xff800000u; }
                            nlo = fmaxf(nlo, __uint_as_float(ml[tl].x)); nhi = fmaxf(nhi, __uint_as_float(ml[tl].z));
                        }
                        nlo = nlo > Mlo + REF_SLACK ? nlo : Mlo; nhi = nhi > Mhi + REF_SLACK ? nhi : Mhi;
                        const float rlo = ex2(Mlo - nlo), rhi = ex2(Mhi - nhi);
                        Mlo = nlo; Mhi = nhi; Llo *= rlo; Lhi *= rhi;
#pragma unroll
                        for (int i = 0; i < 4; i++) {
                            acc[i][0] = (acc[i][0] + acc2[i][0]) * rlo; acc[i][1] = (acc[i][1] + acc2[i][1]) * rlo;
                            acc[i][2] = (acc[i][2] + acc2[i][2]) * rhi; acc[i][3] = (acc[i][3] + acc2[i][3]) * rhi;
                            acc2[i][0] = acc2[i][1] = acc2[i][2] = acc2[i][3] = 0.f;
                        }
#pragma unroll
                        for (int tl = 0; tl < CL; tl++) {
                            flo[tl] = ex2(__uint_as_float(ml[tl].x) - Mlo); fhi[tl] = ex2(__uint_as_float(ml[tl].z) - Mhi);
                            Llo += flo[tl] * __uint_as_float(ml[tl].y); Lhi += fhi[tl] * __uint_as_float(ml[tl].w);
                        }
                    }
                }
                if (stdref) {
#pragma unroll
                    for (int tl = 0; tl < CL; tl++) {
                        if (tl >= 2 && (tl & ~1) >= nt) break;
                        const uint4 pv = lds128(ppb + tl * 512);
                        uint32_t v0[4], v1[4];
                        ldsm4t(v0, va[tl >> 1] + (tl & 1) * 2048 + c0); ldsm4t(v1, va[tl >> 1] + (tl & 1) * 2048 + c1);
                        const uint32_t pa[4] = {pv.x, pv.y, pv.z, pv.w};
                        if (tl & 1) { mma16816(acc2[0], pa, v0[0], v0[1]); mma16816(acc2[1], pa, v0[2], v0[3]); mma16816(acc2[2], pa, v1[0], v1[1]); mma16816(acc2[3], pa, v1[2], v1[3]); }
                        else { mma16816(acc[0], pa, v0[0], v0[1]); mma16816(acc[1], pa, v0[2], v0[3]); mma16816(acc[2], pa, v1[0], v1[1]); mma16816(acc[3], pa, v1[2], v1[3]); }
                    }
                } else {
#pragma unroll
                    for (int tl = 0; tl < CL; tl++) {
                        const uint4 pv = lds128(ppb + (tl < nt ? tl : 0) * 512);
                        uint32_t v0[4], v1[4];
                        ldsm4t(v0, va[tl >> 1] + (tl & 1) * 2048 + c0); ldsm4t(v1, va[tl >> 1] + (tl & 1) * 2048 + c1);
                        const uint32_t pa[4] = {pv.x, pv.y, pv.z, pv.w};
                        float tt[4][4];
#pragma unroll
                        for (int i = 0; i < 4; i++) { tt[i][0] = tt[i][1] = tt[i][2] = tt[i][3] = 0.f; }
                        mma16816(tt[0], pa, v0[0], v0[1]); mma16816(tt[1], pa, v0[2], v0[3]); mma16816(tt[2], pa, v1[0], v1[1]); mma16816(tt[3], pa, v1[2], v1[3]);
#pragma unroll
                        for (int i = 0; i < 4; i++) {
                            acc[i][0] += flo[tl] * tt[i][0]; acc[i][1] += flo[tl] * tt[i][1]; acc[i][2] += fhi[tl] * tt[i][2]; acc[i][3] += fhi[tl] * tt[i][3];
                        }
                    }
                }
                if (lane == 0) mbar_arrive(BAR(B_REL + 1 + j));
                if (warp == 4 && lane == 0) { TSTAMP2(38 + j); }
            }
            const float ilo = __fdividef(1.f, Llo), ihi = __fdividef(1.f, Lhi);
            const uint32_t wlo = __float_as_uint(Mlo + __log2f(Llo)), whi = __float_as_uint(Mhi + __log2f(Lhi));
#pragma unroll
            for (int q = 0; q < 2; q++) {
                st_tag2(gp + q * 8, mk(pack_bf16((acc[2 * q][0] + acc2[2 * q][0]) * ilo, (acc[2 * q][1] + acc2[2 * q][1]) * ilo), tag | (wlo & 0xffff0000u)),
                                    mk(pack_bf16((acc[2 * q + 1][0] + acc2[2 * q + 1][0]) * ilo, (acc[2 * q + 1][1] + acc2[2 * q + 1][1]) * ilo), tag | (wlo << 16)));
                st_tag2(gp + q * 8 + 8 * (DC_ / 2), mk(pack_bf16((acc[2 * q][2] + acc2[2 * q][2]) * ihi, (acc[2 * q][3] + acc2[2 * q][3]) * ihi), tag | (whi & 0xffff0000u)),
                                                    mk(pack_bf16((acc[2 * q + 1][2] + acc2[2 * q + 1][2]) * ihi, (acc[2 * q + 1][3] + acc2[2 * q + 1][3]) * ihi), tag | (whi << 16)));
            }
            if (warp == 4 && lane == 0) { TSTAMP2(5); mbar_arrive(BAR(GO_D)); }
        }
        {
            uint32_t wa[MAXUB][2][4];
            const uint32_t aoff = (warp >> 1) * 2048 + ((mi >> 1) * 8 + r) * 128;
            const int ch0 = (warp & 1) * 4 + (mi & 1);
            auto load_unit = [&](int ks) {
                if (ks < nB) {
                    WAITG(G_UV + ks);
                    const uint32_t ua = SLOT(G_UV + ks) + aoff;
                    ldsm4t(wa[ks][0], ua + ((ch0 ^ r) << 4));
                    ldsm4t(wa[ks][1], ua + (((ch0 + 2) ^ r) << 4));
                } else {
#pragma unroll
                    for (int k = 0; k < 4; k++) { wa[ks][0][k] = 0u; wa[ks][1][k] = 0u; }
                }
            };
#pragma unroll
            for (int ks = 0; ks < MLA_KPRE; ks++) load_unit(ks);
            TSTAMP(50);
            if (warp < 4) recv_ctxl(tid);
            TSTAMP(6);
            const unsigned char* vb = sp + S::VBD + (t * 4 + (g & 3)) * 8;
            const int hh = t ? h2 : h1;
            u64* gc = GS(O_CTX + ((b - P.firstB[hh]) * H_ + hh) * D_ + warp * 32 + g);
            u64* ga = GS(O_ACTX + hh * D_ + warp * 32 + g);
            asm volatile("bar.sync 2, 288;" ::: "memory");
            TSTAMP(51);
            float c[4][4];
#pragma unroll
            for (int i = 0; i < 4; i++) { c[i][0] = c[i][1] = c[i][2] = c[i][3] = 0.f; }
#pragma unroll
            for (int ks = 0; ks < MAXUB; ks++) {
                if (ks >= MLA_KPRE) load_unit(ks);
                const uint2 bw = *reinterpret_cast<const uint2*>(vb + ks * 128);
                const uint32_t b0 = g < 4 ? bw.x : 0u, b1 = g < 4 ? bw.y : 0u;
                mma16816(c[(ks & 1) * 2], wa[ks][0], b0, b1);
                mma16816(c[(ks & 1) * 2 + 1], wa[ks][1], b0, b1);
            }
            if (lane == 0) mbar_arrive(BAR(B_REL + 6));
            if (t == 0 || (t == 1 && h2 != h1)) {
                const float o0 = (c[0][0] + c[2][0]) + (c[0][1] + c[2][1]), o1 = (c[0][2] + c[2][2]) + (c[0][3] + c[2][3]);
                const float o2 = (c[1][0] + c[3][0]) + (c[1][1] + c[3][1]), o3 = (c[1][2] + c[3][2]) + (c[1][3] + c[3][3]);
                red_add(ga, acc_enc(o0)); red_add(ga + 8, acc_enc(o1)); red_add(ga + 16, acc_enc(o2)); red_add(ga + 24, acc_enc(o3));
                st_tag1(gc, mkf(o0, tag)); st_tag1(gc + 8, mkf(o1, tag)); st_tag1(gc + 16, mkf(o2, tag)); st_tag1(gc + 24, mkf(o3, tag));
            }
            if (tid == 0) mbar_arrive(BAR(GO_CTX));
            TSTAMP(7);
        }
        {
            uint32_t wa[4][3][4];
            uint32_t rsd[4];
#pragma unroll
            for (int i = 0; i < 4; i++) rsd[i] = mapa(sb, min((warp >> 2) + 2 * i, 6));
            const uint32_t rso = S::RS + rank * 256 + ((warp & 3) * 8 + g) * 8;
            const uint32_t vb = sb + S::VBE + (g & 1) * 144 + 4 * t;
#pragma unroll
            for (int ks = 0; ks < 3; ks++) {
                if (ks * 2 < nE) WAITG(G_WO + ks * 2);
                if (ks * 2 + 1 < nE) WAITG(G_WO + ks * 2 + 1);
                const uint32_t ua = SLOT(G_WO + min(ks * 2 + (mi >> 1), nE - 1)) + r * 128;
#pragma unroll
                for (int i = 0; i < 4; i++) {
                    const int mt = min(warp + 8 * i, 27);
                    const int ch = (mt & 3) * 2 + (mi & 1);
                    ldsm4t(wa[i][ks], ua + (mt >> 2) * 1024 + ((ch ^ r) << 4));
                }
            }
            mbar_wait(BAR(B_E));
            uint32_t bv[3][2];
#pragma unroll
            for (int ks = 0; ks < 3; ks++) {
                bv[ks][0] = lds32(vb + ks * 32); bv[ks][1] = lds32(vb + ks * 32 + 16);
                if (g >= 2) { bv[ks][0] = 0u; bv[ks][1] = 0u; }
            }
            float c[4][4];
#pragma unroll
            for (int i = 0; i < 4; i++) { c[i][0] = c[i][1] = c[i][2] = c[i][3] = 0.f; }
#pragma unroll
            for (int ks = 0; ks < 3; ks++)
#pragma unroll
                for (int i = 0; i < 4; i++) mma16816(c[i], wa[i][ks], bv[ks][0], bv[ks][1]);
#pragma unroll
            for (int i = 0; i < 4; i++)
                if (t == 0 && warp + 8 * i < 28) st_async_v2(rsd[i] + rso, __float_as_uint(c[i][0] + c[i][1]), __float_as_uint(c[i][2] + c[i][3]), rsd[i] + S::BARS + 8 * B_RS1);
            TSTAMP(8);
        }
        if (isF) {
            uint32_t wg[4][4], wu[4][4], wd[4][4];
            uint32_t rsd[4];
#pragma unroll
            for (int i = 0; i < 4; i++) rsd[i] = mapa(sb, min((warp >> 2) + 2 * i, 6));
            const uint32_t rso = S::RS + 2048 + rank * 256 + ((warp & 3) * 8 + g) * 8;
            const int nh = g < 2 ? (warp < 4 ? 4 : 3) : 0;
#pragma unroll
            for (int i = 0; i < 4; i++) WAITG(G_FG + i);
#pragma unroll
            for (int i = 0; i < 4; i++) {
                const int ks = min(warp + 8 * i, 27);
                const int row = ks * 16 + (mi >> 1) * 8 + r;
                const int hb = row >= 224, rr = row - hb * 224;
                const uint32_t o = rr * 32 + ((((mi & 1) ^ (rr >> 2)) & 1) << 4);
                ldsm4t(wg[i], SLOT(G_FG + hb) + o);
                ldsm4t(wu[i], SLOT(G_FG + 2 + hb) + o);
            }
            WAITG(G_WD); WAITG(G_WD + 1);
#pragma unroll
            for (int i = 0; i < 4; i++) {
                const int mt = min(warp + 8 * i, 27);
                const int ch = (mt & 3) * 2 + (mi & 1);
                ldsm4t(wd[i], SLOT(G_WD + (mi >> 1)) + (mt >> 2) * 1024 + r * 128 + ((ch ^ r) << 4));
            }
            uint2 hf[4];
            mbar_wait(BAR(B_FAC));
#pragma unroll
            for (int i = 0; i < 4; i++) {
                hf[i] = *reinterpret_cast<const uint2*>(sp + S::VBF + (((warp + 8 * (i < nh ? i : 0)) * 4 + t) * 2 + (g & 1)) * 8);
                if (i >= nh) hf[i] = make_uint2(0u, 0u);
            }
            TSTAMP(19);
            float cg[2][4], cu[2][4];
#pragma unroll
            for (int i = 0; i < 2; i++) { cg[i][0] = cg[i][1] = cg[i][2] = cg[i][3] = 0.f; cu[i][0] = cu[i][1] = cu[i][2] = cu[i][3] = 0.f; }
#pragma unroll
            for (int i = 0; i < 4; i++) {
                uint32_t b0 = hf[i].x, b1 = hf[i].y;
                if (g == 2 && warp + 8 * i < 28) { b0 = b1 = 0x3f803f80u; }
                mma16816(cg[i & 1], wg[i], b0, b1);
                mma16816(cu[i & 1], wu[i], b0, b1);
            }
            float* red = reinterpret_cast<float*>(sp + S::RED);
            if (t < 2) {
                float* rp = red + warp * 64 + t * 32 + g;
                rp[0] = (cg[0][0] + cg[1][0]) + (cg[0][1] + cg[1][1]); rp[8] = (cg[0][2] + cg[1][2]) + (cg[0][3] + cg[1][3]);
                rp[16] = (cu[0][0] + cu[1][0]) + (cu[0][1] + cu[1][1]); rp[24] = (cu[0][2] + cu[1][2]) + (cu[0][3] + cu[1][3]);
            }
            bar_compute();
            float rv[8], rc[8];
#pragma unroll
            for (int w = 0; w < 8; w++) { rv[w] = red[w * 64 + lane]; rc[w] = red[w * 64 + 32 + lane]; }
            TSTAMP(60);
            mbar_wait(BAR(B_F2));
            TSTAMP(61);
            float2 st;
            {
                float s1 = 0.f, s2 = 0.f;
#pragma unroll
                for (int i = 0; i < 7; i++) { const float2 p = *reinterpret_cast<const float2*>(sp + S::STAT + 64 + i * 8); s1 += p.x; s2 += p.y; }
                st.x = s1 * (1.f / M_);
                st.y = rsqrtf(fmaxf(s2 * (1.f / M_) - st.x * st.x, 0.f) + 1e-5f);
            }
            const float sv = ((rv[0] + rv[1]) + (rv[2] + rv[3])) + ((rv[4] + rv[5]) + (rv[6] + rv[7]));
            const float sc = ((rc[0] + rc[1]) + (rc[2] + rc[3])) + ((rc[4] + rc[5]) + (rc[6] + rc[7]));
            const float v = (sv - st.x * sc) * st.y;
            const float uu = __shfl_down_sync(0xffffffffu, v, 16);
            const float av = __fdividef(uu, 1.f + ex2(-1.4426950408889634f * v));
            const float a0 = __shfl_sync(0xffffffffu, av, 2 * t), a1 = __shfl_sync(0xffffffffu, av, 2 * t + 1);
            const float a2 = __shfl_sync(0xffffffffu, av, 2 * t + 8), a3 = __shfl_sync(0xffffffffu, av, 2 * t + 9);
            uint32_t h0, l0, h1b, l1b;
            split2(a0, a1, h0, l0); split2(a2, a3, h1b, l1b);
            const uint32_t b0 = g == 0 ? h0 : (g == 1 ? l0 : 0u), b1 = g == 0 ? h1b : (g == 1 ? l1b : 0u);
#pragma unroll
            for (int i = 0; i < 4; i++) {
                float c[4] = {0.f, 0.f, 0.f, 0.f};
                mma16816(c, wd[i], b0, b1);
                if (t == 0 && warp + 8 * i < 28) st_async_v2(rsd[i] + rso, __float_as_uint(c[0] + c[1]), __float_as_uint(c[2] + c[3]), rsd[i] + S::BARS + 8 * B_RS2);
            }
            TSTAMP(9);
        }
    }
}

constexpr int FB_Q = 0, FB_QA = FB_Q + H_ * D_, FB_S = FB_QA + H_ * DC_, FB_CL = FB_S + H_ * SK_, FB_CTX = FB_CL + H_ * DC_,
              FB_H = FB_CTX + H_ * D_, FB_A = FB_H + 512, FB_END = FB_A + F_;
static_assert(FB_END <= 2 * O_EPOCH, "fallback scratch");
__device__ __forceinline__ float* fbs() { return reinterpret_cast<float*>(g_s); }
__device__ __forceinline__ float bsum(float v, float* red) {
    v = wsum(v);
    __syncthreads();
    if ((threadIdx.x & 31) == 0) red[threadIdx.x >> 5] = v;
    __syncthreads();
    float s = 0.f;
    for (int i = 0; i < (int)(blockDim.x >> 5); i++) s += red[i];
    return s;
}
template <bool GLU>
__global__ void fb_ln_gemv(const __nv_bfloat16* xb, const float* xf, const __nv_bfloat16* w0, const __nv_bfloat16* w1, int N, float* y) {
    __shared__ float xs[M_], red[8];
    float s = 0.f;
    for (int i = threadIdx.x; i < M_; i += blockDim.x) { xs[i] = xb ? __bfloat162float(xb[i]) : xf[i]; s += xs[i]; }
    const float mean = bsum(s, red) * (1.f / M_);
    float vs = 0.f;
    for (int i = threadIdx.x; i < M_; i += blockDim.x) { const float d = xs[i] - mean; vs += d * d; }
    const float rstd = rsqrtf(bsum(vs, red) * (1.f / M_) + 1e-5f);
    const int n = blockIdx.x * blockDim.x + threadIdx.x;
    float a = 0.f, u = 0.f;
    for (int m = 0; m < M_; m++) {
        const float xn = (xs[m] - mean) * rstd;
        a += xn * __bfloat162float(w0[(size_t)m * N + n]);
        if (GLU) u += xn * __bfloat162float(w1[(size_t)m * N + n]);
    }
    y[n] = GLU ? u / (1.f + __expf(-a)) : a;
}
__global__ void fb_qabs(const __nv_bfloat16* wuk) {
    const int row = blockIdx.x * 8 + (threadIdx.x >> 5), lane = threadIdx.x & 31, h = row & 15, c = row >> 4;
    float s = 0.f;
    for (int d = lane; d < D_; d += 32) s += fbs()[FB_Q + h * D_ + d] * __bfloat162float(wuk[(size_t)row * D_ + d]);
    s = wsum(s);
    if (lane == 0) fbs()[FB_QA + h * DC_ + c] = s * 0.0625f;
}
__global__ void fb_scores(const __nv_bfloat16* ckv) {
    const int k = blockIdx.x * 8 + (threadIdx.x >> 5), lane = threadIdx.x & 31;
    float s[H_];
#pragma unroll
    for (int h = 0; h < H_; h++) s[h] = 0.f;
    for (int c = lane; c < DC_; c += 32) {
        const float v = __bfloat162float(ckv[(size_t)k * DC_ + c]);
#pragma unroll
        for (int h = 0; h < H_; h++) s[h] += v * fbs()[FB_QA + h * DC_ + c];
    }
#pragma unroll
    for (int h = 0; h < H_; h++) { const float t = wsum(s[h]); if (lane == 0) fbs()[FB_S + h * SK_ + k] = t; }
}
__global__ void fb_softmax() {
    __shared__ float red[8];
    float* s = fbs() + FB_S + blockIdx.x * SK_;
    float m = -INFINITY;
    for (int k = threadIdx.x; k < SK_; k += 256) m = fmaxf(m, s[k]);
#pragma unroll
    for (int o = 16; o > 0; o >>= 1) m = fmaxf(m, __shfl_xor_sync(0xffffffffu, m, o));
    if ((threadIdx.x & 31) == 0) red[threadIdx.x >> 5] = m;
    __syncthreads();
    for (int i = 0; i < 8; i++) m = fmaxf(m, red[i]);
    float l = 0.f;
    for (int k = threadIdx.x; k < SK_; k += 256) { const float e = __expf(s[k] - m); s[k] = e; l += e; }
    l = 1.f / bsum(l, red);
    for (int k = threadIdx.x; k < SK_; k += 256) s[k] *= l;
}
__global__ void fb_ctxl(const __nv_bfloat16* ckv) {
    __shared__ float part[8][H_][32];
    const int lane = threadIdx.x & 31, w = threadIdx.x >> 5, c = blockIdx.x * 32 + lane;
    float a[H_];
#pragma unroll
    for (int h = 0; h < H_; h++) a[h] = 0.f;
    for (int k = w; k < SK_; k += 8) {
        const float v = __bfloat162float(ckv[(size_t)k * DC_ + c]);
#pragma unroll
        for (int h = 0; h < H_; h++) a[h] += v * fbs()[FB_S + h * SK_ + k];
    }
#pragma unroll
    for (int h = 0; h < H_; h++) part[w][h][lane] = a[h];
    __syncthreads();
    for (int h = w; h < H_; h += 8) {
        float s = 0.f;
        for (int i = 0; i < 8; i++) s += part[i][h][lane];
        fbs()[FB_CL + h * DC_ + c] = s;
    }
}
__global__ void fb_ctx(const __nv_bfloat16* wuv) {
    const int h = blockIdx.x, d = threadIdx.x;
    float s = 0.f;
    for (int c = 0; c < DC_; c++) s += fbs()[FB_CL + h * DC_ + c] * __bfloat162float(wuv[((size_t)c * H_ + h) * D_ + d]);
    fbs()[FB_CTX + h * D_ + d] = s;
}
__global__ void fb_gemv_res(const float* v, int K, const __nv_bfloat16* w, const __nv_bfloat16* bb, const float* bf, float* yf, __nv_bfloat16* yb) {
    const int n = blockIdx.x * blockDim.x + threadIdx.x;
    float s = bb ? __bfloat162float(bb[n]) : bf[n];
    for (int k = 0; k < K; k++) s += v[k] * __bfloat162float(w[(size_t)k * M_ + n]);
    if (yf) yf[n] = s; else yb[n] = __float2bfloat16(s);
}
void launch_fallback(void* const* d_in, void* d_out) {
    typedef const __nv_bfloat16* cb;
    float* sc = nullptr;
    cudaGetSymbolAddress((void**)&sc, g_s);
    cudaStream_t st = cudaStreamPerThread;
    fb_ln_gemv<false><<<16, 256, 0, st>>>((cb)d_in[0], nullptr, (cb)d_in[2], nullptr, H_ * D_, sc + FB_Q);
    fb_qabs<<<H_ * DC_ / 8, 256, 0, st>>>((cb)d_in[3]);
    fb_scores<<<SK_ / 8, 256, 0, st>>>((cb)d_in[1]);
    fb_softmax<<<H_, 256, 0, st>>>();
    fb_ctxl<<<DC_ / 32, 256, 0, st>>>((cb)d_in[1]);
    fb_ctx<<<H_, D_, 0, st>>>((cb)d_in[4]);
    fb_gemv_res<<<7, 64, 0, st>>>(sc + FB_CTX, H_ * D_, (cb)d_in[5], (cb)d_in[0], nullptr, sc + FB_H, nullptr);
    fb_ln_gemv<true><<<7, 256, 0, st>>>(nullptr, sc + FB_H, (cb)d_in[7], (cb)d_in[8], F_, sc + FB_A);
    fb_gemv_res<<<7, 64, 0, st>>>(sc + FB_A, F_, (cb)d_in[9], nullptr, sc + FB_H, nullptr, (__nv_bfloat16*)d_out);
}

typedef CUresult (*EncodeFn)(CUtensorMap*, CUtensorMapDataType, cuuint32_t, void*, const cuuint64_t*, const cuuint64_t*, const cuuint32_t*,
                             const cuuint32_t*, CUtensorMapInterleave, CUtensorMapSwizzle, CUtensorMapL2promotion, CUtensorMapFloatOOBfill);

struct HostState {
    bool ready;
    int CL;
    const void* ptrs[10];
    Maps tm;
    Params P;
    int smem;
};
HostState g_hs;

bool encode(EncodeFn fn, CUtensorMap* tm, const void* base, const cuuint64_t* dims, const cuuint64_t* strides, const cuuint32_t* box, CUtensorMapSwizzle sw) {
    cuuint32_t es[4] = {1, 1, 1, 1};
    return fn(tm, CU_TENSOR_MAP_DATA_TYPE_BFLOAT16, 4, const_cast<void*>(base), dims, strides, box, es, CU_TENSOR_MAP_INTERLEAVE_NONE, sw,
              CU_TENSOR_MAP_L2_PROMOTION_L2_128B, CU_TENSOR_MAP_FLOAT_OOB_FILL_NONE) == CUDA_SUCCESS;
}

bool plan(HostState& hs, int CL, int NC) {
    Params& P = hs.P;
    const int G = CL * NC;
    if (G < NFCTA || G > MAXG || NC > MAXNC) return false;
    P.G = G; P.NC = NC;
    P.qB = 1024 / G; P.rB = 1024 % G;
    P.qE = 512 / G; P.rE = 512 % G;
    P.lB = G - P.rB; P.lE = P.lB - P.rE > 0 ? P.lB - P.rE : 0;
    const int NKG = SK_ / (CL * 4);
    P.qK = NKG / NC; P.rK = NKG % NC;
    const int mB = P.qB + (P.rB > 0), mE = P.qE + (P.rE > 0), mK = P.qK + (P.rK > 0);
    if (mB > MAXUB || mE > 5 || (mK + 3) / 4 > MAXCH || 2 * mB + mK + 2 * mE + 6 > MAXGR || mE + mB > NSLOT || P.qE < 4) return false;
    for (int h = 0; h < H_; h++) {
        int first = -1, last = -1;
        for (int b = 0; b < G; b++) {
            const int u0 = b * P.qB + (b > P.lB ? b - P.lB : 0), u1 = u0 + P.qB + (b >= P.lB);
            if (u0 < 64 * (h + 1) && u1 > 64 * h) { if (first < 0) first = b; last = b; }
        }
        P.firstB[h] = (unsigned char)first; P.nslot[h] = (unsigned char)(last - first + 1);
        if (last - first + 1 > MAXSLOT) return false;
    }
    return true;
}

template <int CL> int max_clusters() {
    const int smem = SM<CL>::END + 1024;
    if (cudaFuncSetAttribute(mla_kernel<CL>, cudaFuncAttributeMaxDynamicSharedMemorySize, smem) != cudaSuccess) { cudaGetLastError(); return 0; }
    cudaLaunchConfig_t cfg = {};
    cfg.gridDim = dim3(CL * 16); cfg.blockDim = dim3(NTHREADS); cfg.dynamicSmemBytes = smem;
    cudaLaunchAttribute at[1];
    at[0].id = cudaLaunchAttributeClusterDimension; at[0].val.clusterDim.x = CL; at[0].val.clusterDim.y = 1; at[0].val.clusterDim.z = 1;
    cfg.attrs = at; cfg.numAttrs = 1;
    int n = 0;
    if (cudaOccupancyMaxActiveClusters(&n, mla_kernel<CL>, &cfg) != cudaSuccess) { cudaGetLastError(); return 0; }
    return n;
}

template <int CL> void launch(HostState& hs) {
    cudaLaunchConfig_t cfg = {};
    cfg.gridDim = dim3(hs.P.G); cfg.blockDim = dim3(NTHREADS); cfg.dynamicSmemBytes = hs.smem; cfg.stream = cudaStreamPerThread;
    cudaLaunchAttribute at[1];
    at[0].id = cudaLaunchAttributeClusterDimension; at[0].val.clusterDim.x = CL; at[0].val.clusterDim.y = 1; at[0].val.clusterDim.z = 1;
    cfg.attrs = at; cfg.numAttrs = 1;
    cudaLaunchKernelEx(&cfg, mla_kernel<CL>, hs.tm, hs.P);
}

void setup(HostState& hs, void* const* d_in, void* d_out) {
    for (int i = 0; i < 10; i++) hs.ptrs[i] = d_in[i];
    hs.P.x = (const __nv_bfloat16*)d_in[0];
    hs.P.out = (__nv_bfloat16*)d_out;
    hs.ready = true;
    hs.CL = 0;
    EncodeFn fn = nullptr;
    cudaDriverEntryPointQueryResult qr;
    if (cudaGetDriverEntryPoint("cuTensorMapEncodeTiled", (void**)&fn, cudaEnableDefault, &qr) != cudaSuccess || !fn) { cudaGetLastError(); return; }
    int n = max_clusters<8>();
    if (n > MAXG / 8) n = MAXG / 8;
    if (!plan(hs, 8, n)) return;
    hs.smem = SM<8>::END + 1024;
    bool ok = true;
    {
        const cuuint32_t kpg = 32;
        cuuint64_t dims[4] = {64, SK_, 16, 1}, st[3] = {DC_ * 2, 128, 128}; cuuint32_t box[4] = {64, kpg, 64 / kpg, 1};
        ok &= encode(fn, &hs.tm.m[1], d_in[1], dims, st, box, CU_TENSOR_MAP_SWIZZLE_128B);
    }
    for (int i = 0; i < 2; i++) {
        cuuint64_t dims[4] = {64, DC_, 4, H_}, st[3] = {H_ * D_ * 2, 128, D_ * 2}; cuuint32_t box[4] = {64, 16, 4, 1};
        ok &= encode(fn, &hs.tm.m[2 + i], d_in[3 + i], dims, st, box, CU_TENSOR_MAP_SWIZZLE_128B);
    }
    {
        cuuint64_t dims[4] = {64, H_ * D_, 7, 1}, st[3] = {M_ * 2, 128, 128}; cuuint32_t box[4] = {64, 8, 7, 1};
        ok &= encode(fn, &hs.tm.m[4], d_in[5], dims, st, box, CU_TENSOR_MAP_SWIZZLE_128B);
    }
    for (int i = 0; i < 2; i++) {
        cuuint64_t dims[4] = {F_, M_, 1, 1}, st[3] = {F_ * 2, 128, 128}; cuuint32_t box[4] = {16, 224, 1, 1};
        ok &= encode(fn, &hs.tm.m[5 + i], d_in[7 + i], dims, st, box, CU_TENSOR_MAP_SWIZZLE_32B);
    }
    {
        cuuint64_t dims[4] = {64, F_, 7, 1}, st[3] = {M_ * 2, 128, 128}; cuuint32_t box[4] = {64, 8, 7, 1};
        ok &= encode(fn, &hs.tm.m[7], d_in[9], dims, st, box, CU_TENSOR_MAP_SWIZZLE_128B);
    }
    {
        cuuint64_t dims[4] = {H_ * D_, M_, 1, 1}, st[3] = {H_ * D_ * 2, 128, 128}; cuuint32_t box[4] = {16, 224, 1, 1};
        ok &= encode(fn, &hs.tm.m[0], d_in[2], dims, st, box, CU_TENSOR_MAP_SWIZZLE_32B);
    }
    if (ok) hs.CL = 8;
}

}

extern "C" void kernel_launch(void* const* d_in, const int* in_sizes, int n_in, void* d_out, int out_size) {
    HostState& hs = g_hs;
    bool same = hs.ready && hs.P.out == d_out;
    for (int i = 0; same && i < 10; i++) same = hs.ptrs[i] == d_in[i];
    if (!same) setup(hs, d_in, d_out);
    if (hs.CL == 8) launch<8>(hs);
    else launch_fallback(d_in, d_out);
}
```
